```python
import torch

def _softmax(x, axis=-1):
    return torch.softmax(x, dim=axis)
def _gelu(x):
    return torch.nn.functional.gelu(x, approximate="tanh")
def _silu(x):
    return torch.nn.functional.silu(x)
def _sigmoid(x):
    return torch.sigmoid(x)
def _layernorm(x, axis=-1, eps=1e-5):
    m = x.mean(dim=axis, keepdim=True)
    v = x.var(dim=axis, keepdim=True, unbiased=False)
    return (x - m) / torch.sqrt(v + eps)
def _scatter_add(tgt, idx, src, axis=0):
    return tgt.clone().index_add_(axis, idx, src)
def _segment_sum(src, seg, n):
    out = torch.zeros((n,) + src.shape[1:], dtype=src.dtype)
    return out.index_add_(0, seg, src)
def _pad(x, pw):
    flat = tuple(v for pair in reversed(pw) for v in pair)
    return torch.nn.functional.pad(x, flat)

kernel_name = 'standalone__weight_only_int_squeezellm__prompt'

def setup_inputs():

    _w = (lambda a: (lambda t: t.to(torch.bfloat16) if t.is_floating_point() else t)(torch.as_tensor(a)))
    B, S, D, F = 1, 2048, 1024, 3584
    bits = 8 if (2 <= 8 <= 4) else 4
    L = 2 ** bits
    qw = torch.randint(0, L, (D, F)).to(torch.int64)
    lut = (lambda *s: torch.randn(*s, dtype=torch.bfloat16) * 0.05)(L, F)
    return {
        "x": _w((lambda *s: torch.randn(*s, dtype=torch.bfloat16) * 0.05)(B, S, D)),
        "qw": _w(qw),
        "lut": _w(lut),
    }

def reference(x, qw, lut):
    w = (lambda x, i, axis: torch.take_along_dim(x, i, dim=axis))(lut, qw, axis=0)
    w = (lambda x, dt: x.to(dt))(w, x.dtype)
    return torch.einsum('bsd,df->bsf', x, w)
```

```cpp
#include <cuda_runtime.h>
#include <cuda_bf16.h>
#include <cuda.h>
#include <stdint.h>
#include <stdio.h>

#define LA 2
#define XPROMO CU_TENSOR_MAP_L2_PROMOTION_L2_128B
#define CSPLIT 5
#define FADDPOS 1
#define BSPLIT 4
#define DSPLIT 4
#define FLAGPOS 1
#define RAW1POS 5
#define PIPE 6
#define PR1 1100
#define LK 1
#define PX0 1000
#define PX1 100000
#define R2AT 0
#define R3AT 3
#define R4AT 4
#define W1EARLY 1
#define PR2 1700
#define PSTEP 0
#define PSBASE 0
#define NOW 2
#define R34AT 0
#define R1MODE 1
#define ST2 1
#define PR34 3500
#define DEADT 300
#define PPOLL 2800
#define ALLONLY 0
#define X1POST 0
#define W3FIRST 1
#define W1BY 3
#define W1D 0
#define F2POS 1
#define W2POS 1
#define W2D 0
#define W3D 0
#define W4L2 0
#define R3W1 4
#define VGRAN 32
#define X2POS 0
#define VSPLIT 0
#define NF 4
#define PAIR 0
#define ZPOS 10
#define HARDBASE 1

constexpr int S_ = 2048, D_ = 1024, F_ = 3584;
constexpr int BM = 256, BN = 224, BK = 64;
constexpr int X_BYTES = BM * BK * 2;
constexpr int W_BYTES = BN * BK * 2;
constexpr int CHUNK_BYTES = BN * 16;
constexpr int OFF_X = 0;
constexpr int OFF_W = 3 * X_BYTES;
constexpr int OFF_STG = OFF_W + 3 * W_BYTES;
constexpr int OFF_LUT = OFF_W + 4 * W_BYTES;
constexpr int OFF_BAR = OFF_LUT + 7 * 2048;
constexpr int OFF_PROF = OFF_BAR + 1024;
constexpr int SMEM_BYTES = OFF_PROF + 1024 + 1024;
constexpr int B_FULL = 0;
constexpr int B_XV = 12;
constexpr int B_WF = 17;
constexpr int B_EMPTY = 22;
constexpr int B_DQ = 34;
constexpr int B_SLAB = 42;
constexpr int B_LUT = 46;

__device__ __align__(1024) uint4 g_w[(size_t)F_ * D_ / 8];
__device__ __align__(128) unsigned g_flags[16 * 32];

__device__ __forceinline__ uint32_t smem_u32(const void* p) { return (uint32_t)__cvta_generic_to_shared(p); }
__device__ __forceinline__ void mbar_init(uint32_t bar, uint32_t cnt) { asm volatile("mbarrier.init.shared::cta.b64 [%0], %1;" ::"r"(bar), "r"(cnt) : "memory"); }
__device__ __forceinline__ void mbar_wait(uint32_t bar) {
    asm volatile("{\n.reg .pred p;\nWAIT_LOOP:\nmbarrier.try_wait.parity.shared::cta.b64 p, [%0], 0;\n@p bra WAIT_DONE;\nbra WAIT_LOOP;\nWAIT_DONE:\n}" ::"r"(bar) : "memory");
}
__device__ __forceinline__ void e_arrive(uint32_t bar) {
    asm volatile("{\n.reg .pred p;\nelect.sync _|p, 0xffffffff;\n@p mbarrier.arrive.shared::cta.b64 _, [%0];\n}" ::"r"(bar) : "memory");
}
__device__ __forceinline__ void e_expect(uint32_t bar, uint32_t bytes) {
    asm volatile("{\n.reg .pred p;\nelect.sync _|p, 0xffffffff;\n@p mbarrier.arrive.expect_tx.shared::cta.b64 _, [%0], %1;\n}" ::"r"(bar), "r"(bytes) : "memory");
}
__device__ __forceinline__ void e_tma(uint32_t bar, const CUtensorMap* tm, uint32_t d0, int x0, int y0) {
    asm volatile("{\n.reg .pred p;\nelect.sync _|p, 0xffffffff;\n"
                 "@p cp.async.bulk.tensor.2d.shared::cluster.global.mbarrier::complete_tx::bytes [%2], [%1, {%3, %4}], [%0];\n}"
                 ::"r"(bar), "l"(tm), "r"(d0), "r"(x0), "r"(y0) : "memory");
}
__device__ __forceinline__ void e_bulk(uint32_t bar, uint32_t bytes, uint32_t dst, const void* src) {
    asm volatile("{\n.reg .pred p;\nelect.sync _|p, 0xffffffff;\n"
                 "@p mbarrier.arrive.expect_tx.shared::cta.b64 _, [%0], %1;\n"
                 "@p cp.async.bulk.shared::cluster.global.mbarrier::complete_tx::bytes [%2], [%3], %1, [%0];\n}"
                 ::"r"(bar), "r"(bytes), "r"(dst), "l"(src) : "memory");
}
__device__ __forceinline__ void e_bulk_p(uint32_t on, uint32_t bar, uint32_t bytes, uint32_t dst, const void* src) {
    if (on) asm volatile("{\n.reg .pred p;\nelect.sync _|p, 0xffffffff;\n"
                         "@p cp.async.bulk.shared::cluster.global.mbarrier::complete_tx::bytes [%2], [%3], %1, [%0];\n}"
                         ::"r"(bar), "r"(bytes), "r"(dst), "l"(src) : "memory");
}
__device__ __forceinline__ void e_prefetch2d(const CUtensorMap* tm, int x, int y) {
    asm volatile("{\n.reg .pred p;\nelect.sync _|p, 0xffffffff;\n@p cp.async.bulk.prefetch.tensor.2d.L2.global [%0, {%1, %2}];\n}" ::"l"(tm), "r"(x), "r"(y) : "memory");
}
#define FASTREL 0
__device__ __forceinline__ void e_publish(unsigned* flag) {
    asm volatile("{\n.reg .pred p;\nelect.sync _|p, 0xffffffff;\n@p red.release.gpu.global.add.u32 [%0], 1;\n}" ::"l"(flag) : "memory");
}
__device__ __forceinline__ void e_red(unsigned* flag, unsigned v) {
    asm volatile("{\n.reg .pred p;\nelect.sync _|p, 0xffffffff;\n@p red.relaxed.gpu.global.add.u32 [%0], %1;\n}" ::"l"(flag), "r"(v) : "memory");
}
__device__ __forceinline__ bool mbar_test(uint32_t bar) {
    uint32_t r;
    asm volatile("{\n.reg .pred p;\nmbarrier.test_wait.parity.shared::cta.b64 p, [%1], 0;\nselp.u32 %0, 1, 0, p;\n}" : "=r"(r) : "r"(bar) : "memory");
    return __all_sync(0xffffffff, r != 0);
}
template <int V> struct IC { static constexpr int value = V; };
__device__ __forceinline__ unsigned ld_flag(const unsigned* f) { unsigned v; asm volatile("ld.relaxed.gpu.global.u32 %0, [%1];" : "=r"(v) : "l"(f) : "memory"); return v; }
__device__ __forceinline__ void finish_poll(const unsigned* f, unsigned v, unsigned target) {
    int n = 0;
    while (!__all_sync(0xffffffff, (int)(v - target) >= 0) && ++n < 4000000) v = ld_flag(f);
    asm volatile("fence.acquire.gpu;" ::: "memory");
    asm volatile("fence.proxy.async.global;" ::: "memory");
}
template <typename T> __device__ __forceinline__ T* ptr_add(T* base, uint32_t off) {
    uint64_t r;
    asm("{\n.reg .u32 l, h;\nmov.b64 {l, h}, %1;\nadd.cc.u32 l, l, %2;\naddc.u32 h, h, 0;\nmov.b64 %0, {l, h};\n}" : "=l"(r) : "l"(base), "r"(off));
    return (T*)r;
}
__device__ __forceinline__ void wgmma_fence() { asm volatile("wgmma.fence.sync.aligned;" ::: "memory"); }
__device__ __forceinline__ void wgmma_commit() { asm volatile("wgmma.commit_group.sync.aligned;" ::: "memory"); }
template <int N> __device__ __forceinline__ void wgmma_wait() { asm volatile("wgmma.wait_group.sync.aligned %0;" ::"n"(N) : "memory"); }
__device__ __forceinline__ void wgmma_m64n224k16(float (&d)[112], uint64_t da, uint64_t db, int scale_d) {
    asm volatile(
        "{\n.reg .pred p;\nsetp.ne.b32 p, %114, 0;\n"
        "wgmma.mma_async.sync.aligned.m64n224k16.f32.bf16.bf16 "
        "{%0, %1, %2, %3, %4, %5, %6, %7, %8, %9, %10, %11, %12, %13, %14, %15, "
        "%16, %17, %18, %19, %20, %21, %22, %23, %24, %25, %26, %27, %28, %29, %30, %31, "
        "%32, %33, %34, %35, %36, %37, %38, %39, %40, %41, %42, %43, %44, %45, %46, %47, "
        "%48, %49, %50, %51, %52, %53, %54, %55, %56, %57, %58, %59, %60, %61, %62, %63, "
        "%64, %65, %66, %67, %68, %69, %70, %71, %72, %73, %74, %75, %76, %77, %78, %79, "
        "%80, %81, %82, %83, %84, %85, %86, %87, %88, %89, %90, %91, %92, %93, %94, %95, "
        "%96, %97, %98, %99, %100, %101, %102, %103, %104, %105, %106, %107, %108, %109, %110, %111}, "
        "%112, %113, p, 1, 1, 0, 0;\n}\n"
        : "+f"(d[0]), "+f"(d[1]), "+f"(d[2]), "+f"(d[3]), "+f"(d[4]), "+f"(d[5]), "+f"(d[6]), "+f"(d[7]),
          "+f"(d[8]), "+f"(d[9]), "+f"(d[10]), "+f"(d[11]), "+f"(d[12]), "+f"(d[13]), "+f"(d[14]), "+f"(d[15]),
          "+f"(d[16]), "+f"(d[17]), "+f"(d[18]), "+f"(d[19]), "+f"(d[20]), "+f"(d[21]), "+f"(d[22]), "+f"(d[23]),
          "+f"(d[24]), "+f"(d[25]), "+f"(d[26]), "+f"(d[27]), "+f"(d[28]), "+f"(d[29]), "+f"(d[30]), "+f"(d[31]),
          "+f"(d[32]), "+f"(d[33]), "+f"(d[34]), "+f"(d[35]), "+f"(d[36]), "+f"(d[37]), "+f"(d[38]), "+f"(d[39]),
          "+f"(d[40]), "+f"(d[41]), "+f"(d[42]), "+f"(d[43]), "+f"(d[44]), "+f"(d[45]), "+f"(d[46]), "+f"(d[47]),
          "+f"(d[48]), "+f"(d[49]), "+f"(d[50]), "+f"(d[51]), "+f"(d[52]), "+f"(d[53]), "+f"(d[54]), "+f"(d[55]),
          "+f"(d[56]), "+f"(d[57]), "+f"(d[58]), "+f"(d[59]), "+f"(d[60]), "+f"(d[61]), "+f"(d[62]), "+f"(d[63]),
          "+f"(d[64]), "+f"(d[65]), "+f"(d[66]), "+f"(d[67]), "+f"(d[68]), "+f"(d[69]), "+f"(d[70]), "+f"(d[71]),
          "+f"(d[72]), "+f"(d[73]), "+f"(d[74]), "+f"(d[75]), "+f"(d[76]), "+f"(d[77]), "+f"(d[78]), "+f"(d[79]),
          "+f"(d[80]), "+f"(d[81]), "+f"(d[82]), "+f"(d[83]), "+f"(d[84]), "+f"(d[85]), "+f"(d[86]), "+f"(d[87]),
          "+f"(d[88]), "+f"(d[89]), "+f"(d[90]), "+f"(d[91]), "+f"(d[92]), "+f"(d[93]), "+f"(d[94]), "+f"(d[95]),
          "+f"(d[96]), "+f"(d[97]), "+f"(d[98]), "+f"(d[99]), "+f"(d[100]), "+f"(d[101]), "+f"(d[102]), "+f"(d[103]),
          "+f"(d[104]), "+f"(d[105]), "+f"(d[106]), "+f"(d[107]), "+f"(d[108]), "+f"(d[109]), "+f"(d[110]), "+f"(d[111])
        : "l"(da), "l"(db), "r"(scale_d));
}

__device__ __forceinline__ void wgmma_n128(float (&d)[64], uint64_t da, uint64_t db) {
    asm volatile(
        "wgmma.mma_async.sync.aligned.m64n128k16.f32.bf16.bf16 "
        "{%0, %1, %2, %3, %4, %5, %6, %7, %8, %9, %10, %11, %12, %13, %14, %15, "
        "%16, %17, %18, %19, %20, %21, %22, %23, %24, %25, %26, %27, %28, %29, %30, %31, "
        "%32, %33, %34, %35, %36, %37, %38, %39, %40, %41, %42, %43, %44, %45, %46, %47, "
        "%48, %49, %50, %51, %52, %53, %54, %55, %56, %57, %58, %59, %60, %61, %62, %63}, "
        "%64, %65, 1, 1, 1, 0, 0;\n"
        : "+f"(d[0]), "+f"(d[1]), "+f"(d[2]), "+f"(d[3]), "+f"(d[4]), "+f"(d[5]), "+f"(d[6]), "+f"(d[7]),
          "+f"(d[8]), "+f"(d[9]), "+f"(d[10]), "+f"(d[11]), "+f"(d[12]), "+f"(d[13]), "+f"(d[14]), "+f"(d[15]),
          "+f"(d[16]), "+f"(d[17]), "+f"(d[18]), "+f"(d[19]), "+f"(d[20]), "+f"(d[21]), "+f"(d[22]), "+f"(d[23]),
          "+f"(d[24]), "+f"(d[25]), "+f"(d[26]), "+f"(d[27]), "+f"(d[28]), "+f"(d[29]), "+f"(d[30]), "+f"(d[31]),
          "+f"(d[32]), "+f"(d[33]), "+f"(d[34]), "+f"(d[35]), "+f"(d[36]), "+f"(d[37]), "+f"(d[38]), "+f"(d[39]),
          "+f"(d[40]), "+f"(d[41]), "+f"(d[42]), "+f"(d[43]), "+f"(d[44]), "+f"(d[45]), "+f"(d[46]), "+f"(d[47]),
          "+f"(d[48]), "+f"(d[49]), "+f"(d[50]), "+f"(d[51]), "+f"(d[52]), "+f"(d[53]), "+f"(d[54]), "+f"(d[55]),
          "+f"(d[56]), "+f"(d[57]), "+f"(d[58]), "+f"(d[59]), "+f"(d[60]), "+f"(d[61]), "+f"(d[62]), "+f"(d[63])
        : "l"(da), "l"(db));
}
__device__ __forceinline__ void wgmma_n96(float (&d)[48], uint64_t da, uint64_t db) {
    asm volatile(
        "wgmma.mma_async.sync.aligned.m64n96k16.f32.bf16.bf16 "
        "{%0, %1, %2, %3, %4, %5, %6, %7, %8, %9, %10, %11, %12, %13, %14, %15, "
        "%16, %17, %18, %19, %20, %21, %22, %23, %24, %25, %26, %27, %28, %29, %30, %31, "
        "%32, %33, %34, %35, %36, %37, %38, %39, %40, %41, %42, %43, %44, %45, %46, %47}, "
        "%48, %49, 1, 1, 1, 0, 0;\n"
        : "+f"(d[0]), "+f"(d[1]), "+f"(d[2]), "+f"(d[3]), "+f"(d[4]), "+f"(d[5]), "+f"(d[6]), "+f"(d[7]),
          "+f"(d[8]), "+f"(d[9]), "+f"(d[10]), "+f"(d[11]), "+f"(d[12]), "+f"(d[13]), "+f"(d[14]), "+f"(d[15]),
          "+f"(d[16]), "+f"(d[17]), "+f"(d[18]), "+f"(d[19]), "+f"(d[20]), "+f"(d[21]), "+f"(d[22]), "+f"(d[23]),
          "+f"(d[24]), "+f"(d[25]), "+f"(d[26]), "+f"(d[27]), "+f"(d[28]), "+f"(d[29]), "+f"(d[30]), "+f"(d[31]),
          "+f"(d[32]), "+f"(d[33]), "+f"(d[34]), "+f"(d[35]), "+f"(d[36]), "+f"(d[37]), "+f"(d[38]), "+f"(d[39]),
          "+f"(d[40]), "+f"(d[41]), "+f"(d[42]), "+f"(d[43]), "+f"(d[44]), "+f"(d[45]), "+f"(d[46]), "+f"(d[47])
        : "l"(da), "l"(db));
}

__device__ __forceinline__ uint32_t pack_bf16(float lo, float hi) {
    uint32_t r; asm("cvt.rn.bf16x2.f32 %0, %1, %2;" : "=r"(r) : "f"(hi), "f"(lo)); return r;
}
__device__ __forceinline__ uint32_t lds32(uint32_t a) { uint32_t v; asm volatile("ld.shared.b32 %0, [%1];" : "=r"(v) : "r"(a)); return v; }
__device__ __forceinline__ void sts32(uint32_t a, uint32_t v) { asm volatile("st.shared.b32 [%0], %1;" ::"r"(a), "r"(v) : "memory"); }
__device__ __forceinline__ void sts128(uint32_t a, uint4 v) { asm volatile("st.shared.v4.b32 [%0], {%1,%2,%3,%4};" ::"r"(a), "r"(v.x), "r"(v.y), "r"(v.z), "r"(v.w) : "memory"); }
__device__ __forceinline__ void stg128(void* p, uint4 v) { asm volatile("st.global.v4.b32 [%0], {%1,%2,%3,%4};" ::"l"(p), "r"(v.x), "r"(v.y), "r"(v.z), "r"(v.w) : "memory"); }
__device__ __forceinline__ void cp16(uint32_t dst, const void* src) { asm volatile("cp.async.cg.shared.global [%0], [%1], 16;" ::"r"(dst), "l"(src) : "memory"); }
__device__ __forceinline__ void cp_commit() { asm volatile("cp.async.commit_group;" ::: "memory"); }
template <int N> __device__ __forceinline__ void cp_wait() { asm volatile("cp.async.wait_group %0;" ::"n"(N) : "memory"); }
__device__ __forceinline__ uint4 dequant8(uint32_t raw, uint32_t lut_a) {
    uint32_t v[8];
#pragma unroll
    for (int i = 0; i < 8; i++) v[i] = lds32(raw + i * 128);
#pragma unroll
    for (int i = 0; i < 8; i++) v[i] = lds32(lut_a + v[i] * 128);
    uint4 o;
    o.x = __byte_perm(v[0], v[1], 0x5410); o.y = __byte_perm(v[2], v[3], 0x5410);
    o.z = __byte_perm(v[4], v[5], 0x5410); o.w = __byte_perm(v[6], v[7], 0x5410);
    return o;
}
__device__ __forceinline__ uint32_t prmt(uint32_t a, uint32_t b, uint32_t c) { uint32_t r; asm("prmt.b32 %0, %1, %2, %3;" : "=r"(r) : "r"(a), "r"(b), "r"(c)); return r; }
__device__ __forceinline__ uint4 lookup8_reg(const uint32_t* c, const uint32_t (&T)[8], uint32_t two31) {
    uint32_t o[4];
#pragma unroll
    for (int h = 0; h < 2; h++) {
        const uint32_t sel = c[4 * h] + c[4 * h + 1] * 16 + c[4 * h + 2] * 256 + c[4 * h + 3] * 4096;
        const uint32_t s7 = sel & 0x7777u;
        uint32_t m;
        asm("lop3.b32 %0, %1, %2, 0x3210, 0xEA;" : "=r"(m) : "r"(__umulhi(sel, two31)), "r"(0x4444u));
        const uint32_t lo = prmt(prmt(T[0], T[1], s7), prmt(T[2], T[3], s7), m);
        const uint32_t hi = prmt(prmt(T[4], T[5], s7), prmt(T[6], T[7], s7), m);
        o[2 * h] = prmt(lo, hi, 0x5140u); o[2 * h + 1] = prmt(lo, hi, 0x7362u);
    }
    return make_uint4(o[0], o[1], o[2], o[3]);
}
template <int OFF, int G0, int G1, int N>
__device__ __forceinline__ void store_tile(const float (&acc)[N], __nv_bfloat16* o) {
#pragma unroll
    for (int G = G0; G < G1; G++) {
        uint4 v;
        v.x = pack_bf16(acc[G * 16 + 0], acc[G * 16 + 1]); v.y = pack_bf16(acc[G * 16 + 4], acc[G * 16 + 5]);
        v.z = pack_bf16(acc[G * 16 + 8], acc[G * 16 + 9]); v.w = pack_bf16(acc[G * 16 + 12], acc[G * 16 + 13]);
        stg128(o + OFF + G * 32, v);
        v.x = pack_bf16(acc[G * 16 + 2], acc[G * 16 + 3]); v.y = pack_bf16(acc[G * 16 + 6], acc[G * 16 + 7]);
        v.z = pack_bf16(acc[G * 16 + 10], acc[G * 16 + 11]); v.w = pack_bf16(acc[G * 16 + 14], acc[G * 16 + 15]);
        stg128(o + OFF + 8 * F_ + G * 32, v);
    }
}
constexpr int NROUNDS = 8;
constexpr unsigned long long R_FIRST = 0xFDB97543ull, R_BATCH = 0x60050400ull, R_DOUBLE = 0x7C;
constexpr unsigned long long W_FLAG = 0x600504000ull;
constexpr unsigned L1_MASK = W4L2 ? 0x2A : 0x2E, L2_MASK = W4L2 ? 0x1EA : 0x1E8; constexpr int W12_AT = 8;
constexpr int NFAST = NF;
__device__ __forceinline__ int round_first(int r) { return (int)(R_FIRST >> (4 * r)) & 15; }
__device__ __forceinline__ int round_batch(int r) { return (int)(R_BATCH >> (4 * r)) & 15; }

#define TSK(w, i)
#define TSF(i)
#define TSP(i)
#define TSQ(i)
#define PW 0
#define TS8(i)
#define TSW(w, i)

template <bool HARD>
__global__ void __launch_bounds__(256, 1)
fused_kernel(const int* __restrict__ qw, const unsigned short* __restrict__ lut, __nv_bfloat16* __restrict__ out,
             uint4* __restrict__ wscr, unsigned* __restrict__ flags, const uint32_t two31,
             const __grid_constant__ CUtensorMap tmq, const __grid_constant__ CUtensorMap tmx64, const __grid_constant__ CUtensorMap tmx
) {
    extern __shared__ uint8_t smem_raw[];
    const uint32_t sbase = HARD ? 1024u : (smem_u32(smem_raw) + 1023) & ~1023u;
    const uint32_t bars = sbase + OFF_BAR;
    const int tid = threadIdx.x, lane = tid & 31;
    const int mt = blockIdx.x & 7, g = blockIdx.x >> 3;
    unsigned clk0; asm volatile("mov.u32 %0, %%clock;" : "=r"(clk0));
    constexpr int SLAB_BYTES = 16 * BN * 4, OFF_SLAB0 = OFF_W + 2 * W_BYTES, OFF_SLAB2 = OFF_X + 2 * X_BYTES;
    const int warp = __shfl_sync(0xffffffff, tid >> 5, 0);
    if (tid < 224) {
        const unsigned short* lp = ptr_add(lut, ((lane >> 2) * F_ + g * BN + (tid & ~31) + (lane & 3) * 8) * 2);
        asm volatile("cp.async.cg.shared.global [%0], [%1], 16;\ncp.async.cg.shared.global [%0+512], [%1+57344], 16;\ncp.async.commit_group;"
                     ::"r"(sbase + OFF_STG + (tid >> 5) * 4096 + lane * 16), "l"(lp) : "memory");
    }
    const int sl = (warp + 1) & 3;
    auto load_slab = [&]() {
        e_tma(bars + 8 * (B_SLAB + sl), &tmq, sbase + (sl < 2 ? OFF_SLAB0 : OFF_SLAB2 - 2 * SLAB_BYTES) + sl * SLAB_BYTES, g * BN, sl * 16);
    };
    if (warp >= 4) {
        asm volatile("{\n.reg .pred p;\nelect.sync _|p, 0xffffffff;\n"
                     "@p mbarrier.init.shared::cta.b64 [%0], 1;\n"
                     "@p fence.mbarrier_init.release.cluster;\n"
                     "@p mbarrier.arrive.expect_tx.shared::cta.b64 _, [%0], %1;\n}"
                     ::"r"(bars + 8 * (B_SLAB + sl)), "n"(SLAB_BYTES) : "memory");
        if (sl < NOW) load_slab();
    } else if (warp < 2) {
        asm volatile("{\n.reg .pred p;\nelect.sync _|p, 0xffffffff;\n"
                     "@p mbarrier.init.shared::cta.b64 [%0], %1;\n"
                     "@p fence.mbarrier_init.release.cluster;\n}" ::"r"(bars + 8 * (warp ? B_LUT : B_FULL)), "r"(8 - warp) : "memory");
    }
    asm volatile("bar.sync 1, 256;" ::: "memory");
    TSQ(0);
    const int wg = warp >> 2;

    const int fl = 8 * ((lane & 7) >> 1) + 2 * (lane >> 3) + (lane & 1);
    const uint32_t lut_a = sbase + OFF_LUT + warp * 2048 + lane * 4;
    const uint32_t stg = sbase + OFF_STG + warp * 4096;
    unsigned* myflags = flags + g * 32;
    const uint4* wgrp = wscr + (size_t)g * 128 * BN;
    unsigned target = 0;

    auto issue_x = [&](int s, int slot) {
        e_tma(bars + 8 * (B_FULL + s), &tmx, sbase + OFF_X + slot * X_BYTES, s * BK, mt * BM);
    };
    auto pf_x = [&](int s, int row0) { e_prefetch2d(&tmx64, s * BK, row0); };
    auto issue_xv = [&](int v, int w, uint32_t bar) {
        const uint32_t dst = sbase + OFF_X + (v & 1) * X_BYTES + w * 16384;
        const int k0 = (12 + 2 * (v & 1)) * BK, r0 = mt * BM + w * 128 + ((v >> 1) & 1) * 64;
        e_tma(bar, &tmx64, dst, k0, r0);
        e_tma(bar, &tmx64, dst + 8192, k0 + BK, r0);
    };
    auto issue_w = [&](int s, int slot, int bar) {
        e_bulk(bars + 8 * bar, W_BYTES, sbase + OFF_W + slot * W_BYTES, wgrp + s * 8 * BN);
    };
    auto load_raw = [&](int t) {
        if (t < 16) {
            const int* src = ptr_add(qw, (uint32_t)(((t * BK + mt * 8 + (lane >> 3)) * F_ + g * BN + warp * 32 + (lane & 7) * 4) * 4));
            asm volatile("cp.async.cg.shared.global [%0], [%1], 16;\ncp.async.cg.shared.global [%0+512], [%1+57344], 16;"
                         ::"r"(stg + (t & 3) * 1024 + lane * 16), "l"(src) : "memory");
        }
        cp_commit();
    };
    auto load_blk = [&](int t, int c) {
        const int* src = ptr_add(qw, (uint32_t)(((t * BK + mt * 8 + (lane >> 3)) * F_ + g * BN + c * 32 + (lane & 7) * 4) * 4));
        asm volatile("cp.async.cg.shared.global [%0], [%1], 16;\ncp.async.cg.shared.global [%0+512], [%1+57344], 16;"
                     ::"r"(sbase + OFF_STG + c * 4096 + t * 1024 + lane * 16), "l"(src) : "memory");
    };
    auto foreign = [&](int t) {
        const int c = warp ^ 4;
        stg128(ptr_add(wscr, (uint32_t)(((g * 128 + t * 8 + mt) * BN + c * 32 + lane) * 16)),
               dequant8(sbase + OFF_STG + c * 4096 + t * 1024 + fl * 4, sbase + OFF_LUT + c * 2048 + lane * 4));
        TSW(4, 5);
    };
    auto my_unit = [&](int t) { return ptr_add(wscr, (uint32_t)(((g * 128 + t * 8 + mt) * BN + warp * 32 + lane) * 16)); };
    auto coop = [&](int t) {
        cp_wait<LA - 1>();
        __syncwarp();
        load_raw(t + LA);
        stg128(my_unit(t), dequant8(stg + (t & 3) * 1024 + fl * 4, lut_a));

    };
    auto coop2 = [&](int t) {
        cp_wait<0>();
        __syncwarp();
        if (t < 14) {
            const int* src = ptr_add(qw, (uint32_t)((((t + 2) * BK + mt * 8 + (lane >> 3)) * F_ + g * BN + warp * 32 + (lane & 7) * 4) * 4));
            asm volatile("cp.async.cg.shared.global [%0], [%1], 16;\ncp.async.cg.shared.global [%0+512], [%1+57344], 16;"
                         ::"r"(stg + ((t + 2) & 3) * 1024 + lane * 16), "l"(src) : "memory");
            if (t < 13) asm volatile("cp.async.cg.shared.global [%0], [%1+917504], 16;\ncp.async.cg.shared.global [%0+512], [%1+974848], 16;"
                                     ::"r"(stg + ((t + 3) & 3) * 1024 + lane * 16), "l"(src) : "memory");
            cp_commit();
        }
        uint32_t v[16];
        const uint32_t r0 = stg + (t & 3) * 1024 + fl * 4, r1 = stg + ((t + 1) & 3) * 1024 + fl * 4;
#pragma unroll
        for (int i = 0; i < 8; i++) v[i] = lds32(r0 + i * 128);
#pragma unroll
        for (int i = 0; i < 8; i++) v[8 + i] = lds32(r1 + i * 128);
#pragma unroll
        for (int i = 0; i < 16; i++) v[i] = lds32(lut_a + v[i] * 128);
        uint4* dst = my_unit(t);
        stg128(dst, make_uint4(prmt(v[0], v[1], 0x5410), prmt(v[2], v[3], 0x5410), prmt(v[4], v[5], 0x5410), prmt(v[6], v[7], 0x5410)));
        if (t < 15) stg128(dst + 8 * BN, make_uint4(prmt(v[8], v[9], 0x5410), prmt(v[10], v[11], 0x5410), prmt(v[12], v[13], 0x5410), prmt(v[14], v[15], 0x5410)));
    };
    auto pace = [&](unsigned t) { unsigned c; do { asm volatile("mov.u32 %0, %%clock;" : "=r"(c)); } while (c - clk0 < t); };
    if (warp == 7) {
        TSW(7, 2); TSQ(1);
        if (lane == 0) {
            asm volatile("prefetch.tensormap [%0];" ::"l"(&tmx) : "memory");
            asm volatile("prefetch.tensormap [%0];" ::"l"(&tmx64) : "memory");
        }
        __syncwarp();
        TSW(7, 13); TSQ(3);
        pace(PX0);
        e_expect(bars + 8 * B_FULL, X_BYTES);
        issue_x(0, 0);
        TSQ(4);
        target = (ld_flag(myflags + 6) | 7) + 1;
        TSW(7, 1);
        pace(PR2);
        load_blk(2, 3);
        cp_commit();
        mbar_wait(bars + 8 * B_LUT);
        if (PX1 < 100000) { pace(PX1); issue_x(1, 1); }
        if (F2POS == 0) { cp_wait<0>(); __syncwarp(); foreign(2); }
        mbar_wait(bars + 8 * B_FULL);
        if (PX1 == 100000) issue_x(1, 1);
        if (F2POS == 1) { cp_wait<0>(); __syncwarp(); foreign(2); }
        if (W1BY == 7) {
            if (W1D) { unsigned c, c0; asm volatile("mov.u32 %0, %%clock;" : "=r"(c0)); do { asm volatile("mov.u32 %0, %%clock;" : "=r"(c)); } while (c - c0 < W1D); }
            e_bulk_p(1, bars + 8 * (B_FULL + 1), W_BYTES, sbase + OFF_W + W_BYTES, wgrp + 8 * BN);
            TSW(7, 4);
        }
        if (PX1 == 100001) issue_x(1, 1);
        if (F2POS == 2) { cp_wait<0>(); __syncwarp(); foreign(2); }
        TSW(7, 3);
    } else {
        if (wg == 1 && sl >= NOW) { pace(PSBASE + sl * PSTEP); load_slab(); }
        auto init_bars = [&]() {
            if (lane == 0) {
#pragma unroll
                for (int i = 0; i < 6; i++) {
                    const int b = 1 + warp * 6 + i;
                    if (b < B_SLAB) mbar_init(bars + 8 * b, b < B_DQ ? 1 : 7);
                    if (b < B_XV) asm volatile("mbarrier.arrive.expect_tx.shared::cta.b64 _, [%0], %1;" ::"r"(bars + 8 * b), "r"(X_BYTES + W_BYTES) : "memory");
                }
                asm volatile("fence.mbarrier_init.release.cluster;" ::: "memory");
            }
            __syncwarp();
        };
        init_bars();
        pace(PR1);
        load_raw(1);

        TSW(0, 15);
        uint32_t lv[16], v[32], T[8];
        cp_wait<1>();
        __syncwarp();
#pragma unroll
        for (int i = 0; i < 16; i++) asm volatile("ld.shared.u16 %0, [%1];" : "=r"(lv[i]) : "r"(stg + i * 64 + fl * 2));
#pragma unroll
        for (int i = 0; i < 16; i++) lv[i] = lv[i] ? lv[i] : 0x8000u;
#pragma unroll
        for (int i = 0; i < 4; i++) {
            const uint32_t p01 = prmt(lv[4 * i], lv[4 * i + 1], 0x5140u), p23 = prmt(lv[4 * i + 2], lv[4 * i + 3], 0x5140u);
            T[i] = prmt(p01, p23, 0x5410u); T[4 + i] = prmt(p01, p23, 0x7632u);
        }
        TSW(0, 7);
#pragma unroll
        for (int i = 0; i < 16; i++) sts32(lut_a + i * 128, lv[i]);
        __syncwarp();
        e_arrive(bars + 8 * B_LUT);
        auto more_raw = [&](int j) {
            if (R2AT == j && wg == 1) { load_blk(2, warp); load_blk(2, warp - 4); cp_commit(); }
            if (R3AT == j && wg == 0) load_raw(3);
            if (R3W1 == j && wg == 1) load_raw(3);
        };
        auto own_task = [&](int t) {
            __syncwarp();
            uint32_t c[8];
#pragma unroll
            for (int i = 0; i < 8; i++) c[i] = lds32(stg + t * 1024 + fl * 4 + i * 128);
            uint4 o = lookup8_reg(c, T, two31);
            stg128(my_unit(t), o);
            if (t == 1) { TSW(4, 6); TSW(0, 14); }
        };
        auto raw1_task = [&]() {
            if (wg == 1) cp_wait<(R2AT < 4) + (R3W1 < 4)>(); else cp_wait<(R3AT < 4)>();
            own_task(1);
        };
        auto piece_ld = [&](int j) {
            TSP(j * 8);
            mbar_wait(bars + 8 * (B_SLAB + j));
            TSP(j * 8 + 1);
#pragma unroll
            for (int i = 0; i < 16; i++) v[(j & 1) * 16 + i] = lds32(sbase + (j < 2 ? OFF_SLAB0 : OFF_SLAB2) + (j & 1) * SLAB_BYTES + i * (BN * 4) + (warp * 32 + fl) * 4);
            more_raw(j);
        };
        auto piece_st = [&](int j) {
            const uint32_t dst = sbase + OFF_W + j * 2 * CHUNK_BYTES + (warp * 32 + lane) * 16;
            sts128(dst, lookup8_reg(v + (j & 1) * 16, T, two31));
            sts128(dst + CHUNK_BYTES, lookup8_reg(v + (j & 1) * 16 + 8, T, two31));
            TSP(j * 8 + 2);
            TSW(PW, 8 + j);
        };
        piece_ld(0);
        if (PIPE & 1) piece_ld(1);
        piece_st(0);
        if (!(PIPE & 1)) piece_ld(1);
        if (PIPE & 2) piece_ld(2);
        piece_st(1);
        if (!(PIPE & 2)) piece_ld(2);
        if (PIPE & 4) piece_ld(3);
        piece_st(2);
        if (!(PIPE & 4)) piece_ld(3);
        if (R1MODE == 2 || (R1MODE == 3 && wg == 0)) raw1_task();
        piece_st(3);
        asm volatile("fence.proxy.async.shared::cta;" ::: "memory");
        TSP(27);
        __syncwarp();
        e_arrive(bars + 8 * B_FULL);
        if (R1MODE == 1 || (wg == 1 && R1MODE == 3)) raw1_task();
        more_raw(4);
        if (wg == 1) {
            cp_wait<(R3W1 < 5)>();
            own_task(2);
            if (R34AT == 0) { if (R3W1 == 5) load_raw(3); load_raw(4); }
            mbar_wait(bars + 8 * B_LUT);
            foreign(2);
            if (R34AT == 1) { if (R3W1 == 5) load_raw(3); load_raw(4); }
        }
        TSW(4, 12);
    }

    float acc0[112], acc1[112];
    const uint64_t descA_hi = ((uint64_t)1 << 62) | ((uint64_t)(1024 >> 4) << 32) | ((uint64_t)1 << 16);
    const uint64_t descB_hi = ((uint64_t)(128 >> 4) << 32) | ((uint64_t)(CHUNK_BYTES >> 4) << 16);
    const uint32_t a16 = ((sbase & 0x3FFFF) >> 4) + wg * 1024 + (uint32_t)descA_hi, b16w = (((sbase + OFF_W) & 0x3FFFF) >> 4) + (uint32_t)descB_hi;
    auto dscA = [&](uint32_t lo) { return (descA_hi & 0xFFFFFFFF00000000ull) | lo; };
    auto dscB = [&](uint32_t lo) { return (descB_hi & 0xFFFFFFFF00000000ull) | lo; };
    uint32_t xo = 0, wo = 0, wo_prev = 2 * W_BYTES;
    const uint4* wnext = wgrp + 2 * 8 * BN;
    auto validate = [&](int t, uint32_t wofs) {
        constexpr int NV = VSPLIT == 1 ? 7 : 14;
        const uint32_t u = VSPLIT == 1 ? tid + wg * (W_BYTES / 32 - 128) : tid & 127;
        const uint32_t a = sbase + OFF_W + wofs + u * 16;
        for (int n = 0; n < 2000000; n++) {
            uint32_t m = 0xffffffffu;
#pragma unroll
            for (int i = 0; i < 7; i++) m = min(m, lds32(a + u * 16 + (lane >> 2) * 4 + i * 4096));
            if (__all_sync(0xffffffff, m != 0)) break;
            const uint4* src = ptr_add(wgrp, (uint32_t)((t * 8 * BN + (u & ~31) * 2 + lane) * 16));
#pragma unroll 1
            for (int i = 0; i < 14; i++) cp16(sbase + OFF_W + wofs + ((u & ~31) * 2 + lane + (i >> 1) * 256 + (i & 1) * 32) * 16, src + (i >> 1) * 256 + (i & 1) * 32);
            cp_commit();
            cp_wait<0>();
            asm volatile("fence.proxy.async.shared::cta;" ::: "memory");
            __syncwarp();
        }
    };
    auto batch = [&](int s, bool val) {
        if (val && s == 0) TSP(28);
        mbar_wait(bars + 8 * (B_FULL + s));
        if (val && s == 0) TSP(29);
        if (val && VSPLIT != 2 && wg == 0 && (unsigned)(s - 1) < NFAST) validate(s, wo);
        if (s + wg > 0) asm volatile("bar.sync %0, 256;" ::"r"(2 + wg) : "memory");
        TSW(0, 16 + s); TSW(4, 48 + s); TS8(16 + s);
        const uint32_t al = a16 + (xo >> 4), bl = b16w + (wo >> 4);
        wgmma_fence();
#pragma unroll
        for (int kk = 0; kk < 4; kk++) {
            const uint64_t db = dscB(bl + kk * (2 * CHUNK_BYTES >> 4));
            wgmma_m64n224k16(acc0, dscA(al + kk * 2), db, (s | kk) != 0);
            wgmma_m64n224k16(acc1, dscA(al + kk * 2 + (8192 >> 4)), db, (s | kk) != 0);
        }
        wgmma_commit();
        if (val && VSPLIT && wg == 1 && s < NFAST) { mbar_wait(bars + 8 * (B_FULL + s + 1)); validate(s + 1, 3 * W_BYTES - wo - wo_prev); }
        asm volatile("bar.arrive %0, 256;" ::"r"(3 - wg) : "memory");
        TSW(0, 32 + s); TSW(4, 64 + s);
    };
    auto advance = [&]() {
        wo_prev = wo;
        xo = xo == 2 * X_BYTES ? 0 : xo + X_BYTES;
        wo = wo == 2 * W_BYTES ? 0 : wo + W_BYTES;
        wnext += 8 * BN;
    };
#pragma unroll 1
    for (int s = 0; s < 9; s++) {
        batch(s, true);
        const uint32_t bs = bars + 8 * s;
        if (warp == 7) {
            const int fb = (int)(W_FLAG >> (4 * s)) & 15;
            unsigned* fp = ptr_add(myflags, fb * 4);
            unsigned fv = target;
            const int pb = round_batch(s);
            const uint32_t l1 = (L1_MASK >> s) & 1, l2 = (L2_MASK >> s) & 1;
            if (fb) fv = ld_flag(fp);
            else e_bulk_p(l1 && !pb, bs + 8 * (B_FULL + 2), W_BYTES, sbase + OFF_W + wo_prev, wnext);
            if (s == 0 && X2POS == 0) issue_x(2, 2);
            TSW(7, 112 + s);
            if (s == 0 && X2POS == 1) issue_x(2, 2);
            if (pb) {
                mbar_wait(bars + 8 * (B_DQ + pb));
                mbar_wait(bs + 8 * B_EMPTY);
                e_publish(ptr_add(myflags, pb * 4));
                e_bulk_p(l1, bs + 8 * (B_FULL + 2), W_BYTES, sbase + OFF_W + wo_prev, wnext);
            } else {
                if (fb) {
                    finish_poll(fp, fv, target);
                    e_bulk_p(l1, bs + 8 * (B_FULL + 2), W_BYTES, sbase + OFF_W + wo_prev, wnext);
                }
                mbar_wait(bs + 8 * B_EMPTY);
                if (s == W12_AT) {
                    issue_w(12, 3, B_WF);
                    e_bulk(bars + 8 * (B_WF + 3), W_BYTES / 2, sbase + OFF_LUT, wgrp + 15 * 8 * BN);
                }
            }
            wgmma_wait<0>();
            e_bulk_p(s == 0, bs + 8 * (B_FULL + 2), W_BYTES, sbase + OFF_W + wo_prev, wnext);
            e_bulk_p(l2, bs + 8 * (B_FULL + 3), W_BYTES, sbase + OFF_W + wo, wnext + 8 * BN);
            e_tma(bs + 8 * (B_FULL + 3), &tmx, sbase + OFF_X + xo, (s + 3) * BK, mt * BM);
            TSW(7, 96 + s);
        } else {
            if (s == 0) {
                if (wg == 0) {
                    if (R3AT > 4) load_raw(3);
                    if (warp == W1BY) { e_bulk_p(1, bars + 8 * (B_FULL + 1), W_BYTES, sbase + OFF_W + W_BYTES, wgrp + 8 * BN); TSW(3, 4); }
                    load_raw(4);
                } else if (R34AT == 2) { if (R3W1 == 5) load_raw(3); load_raw(4); }
            }
            const int r = s + wg;
            if (wg == 0 && s < 2) coop(s + 3);
            else if (r < NROUNDS) { if (PAIR) coop2(2 * r + 1); else { coop(2 * r + 1); if (r < 7) coop(2 * r + 2); } }
            if (round_batch(r)) { __syncwarp(); e_arrive(bars + 8 * (B_DQ + round_batch(r))); }
            TSW(0, 80 + s);
            wgmma_wait<0>();
            if (warp == 3) e_arrive(bs + 8 * B_EMPTY);
            if (warp == 2 && (s & 3) == 1) pf_x(s + 4 + (g >> 2), mt * BM + (g & 3) * 64);
        }
        advance();
    }
    auto rezero = [&]() {
        mbar_wait(bars + 8 * (B_FULL + 11));
#pragma unroll
        for (int t = 1; t <= NFAST; t++) stg128(my_unit(t), make_uint4(0, 0, 0, 0));
    };
    {
        batch(9, false);
        if (warp == 7) {
            pf_x(13 + (g >> 2), mt * BM + (g & 3) * 64);
            mbar_wait(bars + 8 * (B_EMPTY + 9));
        } else if (ZPOS == 9) rezero();
        wgmma_wait<0>();
        if (warp == 3) e_arrive(bars + 8 * (B_EMPTY + 9));
        if (warp == 7) {
            issue_w(13, 0, B_WF + 1);
            e_expect(bars + 8 * B_XV, X_BYTES);
            issue_xv(12, 0, bars + 8 * B_XV); issue_xv(12, 1, bars + 8 * B_XV);
        }
        advance();
        batch(10, false);
        if (warp == 7) mbar_wait(bars + 8 * (B_EMPTY + 10)); else if (ZPOS == 10) rezero();
        wgmma_wait<0>();
        if (warp == 3) e_arrive(bars + 8 * (B_EMPTY + 10));
    }
    const int w4 = warp & 3;
    __nv_bfloat16* o = ptr_add(out, (uint32_t)(((mt * BM + wg * 128 + w4 * 16 + (lane >> 2)) * F_ + g * BN + (lane & 3) * 8) * 2));
    auto wofs = [](int st, int kk) -> uint32_t {
        return st < 15 ? OFF_W + (st == 11 ? 2 : st == 12 ? 3 : st - 13) * W_BYTES + kk * 2 * CHUNK_BYTES
                       : kk < 2 ? OFF_LUT + kk * 2 * CHUNK_BYTES : OFF_X + 2 * X_BYTES + (kk - 2) * 16384;
    };
    auto xofs = [](int st, int kk, int r) -> uint32_t {
        return (st == 11 ? 2 * X_BYTES + r * 8192 : ((st - 12) >> 1) * X_BYTES + (st & 1) * 8192) + kk * 32;
    };
    auto launder = [&]() { uint32_t b16 = (sbase & 0x3FFFF) >> 4; asm volatile("mov.u32 %0, %0;" : "+r"(b16)); return b16; };
    auto dA = [&](uint32_t b16, uint32_t ofs) { return (descA_hi & 0xFFFFFFFF00000000ull) | (uint64_t)(b16 + wg * 1024 + (ofs >> 4) + (uint32_t)descA_hi); };
    auto dB = [&](uint32_t b16, uint32_t ofs) { return (descB_hi & 0xFFFFFFFF00000000ull) | (uint64_t)(b16 + (ofs >> 4) + (uint32_t)descB_hi); };
    float lo1[64], hi1[48];
    {
        mbar_wait(bars + 8 * (B_FULL + 11));
        asm volatile("bar.sync %0, 256;" ::"r"(2 + wg) : "memory");
        const uint32_t b16 = launder();
        wgmma_fence();
#pragma unroll
        for (int kk = 0; kk < 4; kk++) wgmma_m64n224k16(acc0, dA(b16, xofs(11, kk, 0)), dB(b16, wofs(11, kk)), 1);
        wgmma_commit();
        asm volatile("bar.arrive %0, 256;" ::"r"(3 - wg) : "memory");
        if (warp == 7) {
            issue_w(14, 1, B_WF + 2);
            e_expect(bars + 8 * (B_XV + 1), X_BYTES);
            issue_xv(13, 0, bars + 8 * (B_XV + 1)); issue_xv(13, 1, bars + 8 * (B_XV + 1));
            mbar_wait(bars + 8 * (B_EMPTY + 11));
        } else if (ZPOS == 11) rezero();
        if (FADDPOS == 0) {
#pragma unroll
            for (int i = 0; i < 64; i++) asm volatile("add.f32 %0, %1, 0f00000000;" : "=f"(lo1[i]) : "f"(acc1[i]));
#pragma unroll
            for (int i = 0; i < 48; i++) asm volatile("add.f32 %0, %1, 0f00000000;" : "=f"(hi1[i]) : "f"(acc1[64 + i]));
        }
        wgmma_wait<0>();
        if (warp == 3) e_arrive(bars + 8 * (B_EMPTY + 11));
        if (warp == 7) {
            e_bulk(bars + 8 * (B_WF + 4), 2 * CHUNK_BYTES, sbase + wofs(15, 2), wgrp + (15 * 8 + 4) * BN);
            e_bulk(bars + 8 * (B_XV + 4), 2 * CHUNK_BYTES, sbase + wofs(15, 3), wgrp + (15 * 8 + 6) * BN);
        }
    }
    {
        asm volatile("bar.sync %0, 256;" ::"r"(2 + wg) : "memory");
        TSK(0, 28); TSF(0);
        const uint32_t b16 = launder();
#pragma unroll
        for (int st = 12; st < 16; st++) {
            if (!(st & 1)) mbar_wait(bars + 8 * (B_XV + ((st - 12) >> 1)));
            mbar_wait(bars + 8 * (B_WF + st - 12));
            if (!(st & 1)) wgmma_fence();
#pragma unroll
            for (int kk = 0; kk < 4; kk++) {
                if (st == 15 && kk >= 2) mbar_wait(bars + 8 * (kk == 2 ? B_WF + 4 : B_XV + 4));
                wgmma_m64n224k16(acc0, dA(b16, xofs(st, kk, 0)), dB(b16, wofs(st, kk)), 1);
            }
            if (st & 1) wgmma_commit();
        }
        asm volatile("bar.arrive %0, 256;" ::"r"(3 - wg) : "memory");
        TSF(1);
        if (FADDPOS == 1) {
#pragma unroll
            for (int i = 0; i < 64; i++) asm volatile("add.f32 %0, %1, 0f00000000;" : "=f"(lo1[i]) : "f"(acc1[i]));
#pragma unroll
            for (int i = 0; i < 48; i++) asm volatile("add.f32 %0, %1, 0f00000000;" : "=f"(hi1[i]) : "f"(acc1[64 + i]));
        }
        wgmma_wait<0>();
        if (w4 == 3) {
            e_expect(bars + 8 * (B_XV + 2 + wg), X_BYTES);
            issue_xv(14, wg, bars + 8 * (B_XV + 2 + wg)); issue_xv(15, wg, bars + 8 * (B_XV + 2 + wg));
        }
        TSF(2);
        store_tile<0, 0, CSPLIT>(acc0, o);
        if (wg == 0) store_tile<0, CSPLIT, 7>(acc0, o);
        TSF(3);
    }
    auto piece = [&](int hi) {
        asm volatile("bar.sync %0, 256;" ::"r"(2 + wg) : "memory");
        TSF(4 + hi * 4);
        const uint32_t b16 = launder();
        wgmma_fence();
#pragma unroll
        for (int st = 11; st < 16; st++) {
            if (!hi && st == 12) mbar_wait(bars + 8 * (B_XV + 2 + wg));
#pragma unroll
            for (int kk = 0; kk < 4; kk++) {
                if (hi) wgmma_n96(hi1, dA(b16, xofs(st, kk, 1)), dB(b16, wofs(st, kk) + 128 * 16));
                else wgmma_n128(lo1, dA(b16, xofs(st, kk, 1)), dB(b16, wofs(st, kk)));
            }
        }
        wgmma_commit();
        if (!(hi && wg == 1)) asm volatile("bar.arrive %0, 256;" ::"r"(3 - wg) : "memory");
        TSF(5 + hi * 4);
    };
    piece(0);
    if (wg == 1) store_tile<0, CSPLIT, 7>(acc0, o);
    wgmma_wait<0>();
    TSF(6);
    if (wg == 0) store_tile<64 * F_, 0, BSPLIT>(lo1, o); else store_tile<64 * F_, 0, DSPLIT>(lo1, o);
    TSF(7);
    piece(1);
    if (wg == 0) store_tile<64 * F_, BSPLIT, 4>(lo1, o); else store_tile<64 * F_, DSPLIT, 4>(lo1, o);
    wgmma_wait<0>();
    TSK(4, 63); TSF(10);
    store_tile<64 * F_ + 128, 0, 3>(hi1, o);
    TSK(4, 77); TSF(11);
}

typedef CUresult (*EncodeTiledFn)(CUtensorMap*, CUtensorMapDataType, cuuint32_t, void*, const cuuint64_t*, const cuuint64_t*, const cuuint32_t*, const cuuint32_t*, CUtensorMapInterleave, CUtensorMapSwizzle, CUtensorMapL2promotion, CUtensorMapFloatOOBfill);

extern "C" void kernel_launch(void* const* d_in, const int* in_sizes, int n_in, void* d_out, int out_size) {
    static EncodeTiledFn enc = nullptr;
    static decltype(&fused_kernel<true>) kern = nullptr;
    static void *p_w = nullptr, *p_flags = nullptr, *p_prof = nullptr;
    if (!enc) {
        void* fn = nullptr; cudaDriverEntryPointQueryResult qr;
        cudaGetDriverEntryPoint("cuTensorMapEncodeTiled", &fn, cudaEnableDefault, &qr);
        enc = (EncodeTiledFn)fn;
        int dev = 0, rsv = 0;
        cudaGetDevice(&dev);
        cudaDeviceGetAttribute(&rsv, cudaDevAttrReservedSharedMemoryPerBlock, dev);
        kern = HARDBASE && rsv == 1024 ? fused_kernel<true> : fused_kernel<false>;
        cudaFuncSetAttribute(kern, cudaFuncAttributeMaxDynamicSharedMemorySize, SMEM_BYTES);
        cudaGetSymbolAddress(&p_w, g_w);
        cudaGetSymbolAddress(&p_flags, g_flags);
    }
    CUtensorMap tmx, tmx64, tmq;
    {
        cuuint64_t gdim[2] = {(cuuint64_t)F_, (cuuint64_t)D_};
        cuuint64_t gstr[1] = {(cuuint64_t)F_ * 4};
        cuuint32_t box[2] = {(cuuint32_t)BN, 16};
        cuuint32_t estr[2] = {1, 1};
        enc(&tmq, CU_TENSOR_MAP_DATA_TYPE_INT32, 2, d_in[1], gdim, gstr, box, estr, CU_TENSOR_MAP_INTERLEAVE_NONE,
            CU_TENSOR_MAP_SWIZZLE_NONE, CU_TENSOR_MAP_L2_PROMOTION_L2_128B, CU_TENSOR_MAP_FLOAT_OOB_FILL_NONE);
    }
    {
        cuuint64_t gdim[2] = {(cuuint64_t)D_, (cuuint64_t)S_};
        cuuint64_t gstr[1] = {(cuuint64_t)D_ * 2};
        cuuint32_t box[2] = {(cuuint32_t)BK, (cuuint32_t)BM};
        cuuint32_t estr[2] = {1, 1};
        enc(&tmx, CU_TENSOR_MAP_DATA_TYPE_BFLOAT16, 2, d_in[0], gdim, gstr, box, estr, CU_TENSOR_MAP_INTERLEAVE_NONE,
            CU_TENSOR_MAP_SWIZZLE_128B, XPROMO, CU_TENSOR_MAP_FLOAT_OOB_FILL_NONE);
        box[1] = 64;
        enc(&tmx64, CU_TENSOR_MAP_DATA_TYPE_BFLOAT16, 2, d_in[0], gdim, gstr, box, estr, CU_TENSOR_MAP_INTERLEAVE_NONE,
            CU_TENSOR_MAP_SWIZZLE_128B, XPROMO, CU_TENSOR_MAP_FLOAT_OOB_FILL_NONE);
    }
    kern<<<128, 256, SMEM_BYTES>>>((const int*)d_in[1], (const unsigned short*)d_in[2], (__nv_bfloat16*)d_out, (uint4*)p_w, (unsigned*)p_flags, 0x80000000u, tmq, tmx64, tmx
    );
    (void)p_prof;
}
```

```cpp
#include <cuda_runtime.h>
#include <cuda_bf16.h>
#include <cuda.h>
#include <stdint.h>
#include <stdio.h>

#define LA 2
#define XPROMO CU_TENSOR_MAP_L2_PROMOTION_L2_128B
#define CSPLIT 5
#define FADDPOS 1
#define BSPLIT 4
#define DSPLIT 4
#define FLAGPOS 1
#define RAW1POS 5
#define PIPE 6
#define PR1 1100
#define LK 1
#define PX0 1000
#define PX1 100000
#define R2AT 0
#define R3AT 3
#define R4AT 4
#define W1EARLY 1
#define PR2 1700
#define PSTEP 0
#define PSBASE 0
#define NOW 2
#define R34AT 0
#define R1MODE 1
#define ST2 1
#define PR34 3500
#define DEADT 300
#define PPOLL 2800
#define ALLONLY 0
#define X1POST 0
#define W3FIRST 1
#define W1BY 3
#define W1D 150
#define F2POS 1
#define W2POS 0
#define W2D 200
#define W3D 0
#define W4L2 0
#define R3W1 4
#define VGRAN 32
#define X2POS 0
#define VSPLIT 0
#define NF 4
#define PAIR 0
#define ZPOS 10
#define PFX 0
#define PFXB 2
#define ASP 12
#define CSP 10
#define BSP 8
#define DSP 6
#define ISTEP 2
#define ISTEP2 2
#define PEEL 1
#define ILV 0
#define R4W0 0
#define HARDBASE 1

constexpr int S_ = 2048, D_ = 1024, F_ = 3584;
constexpr int BM = 256, BN = 224, BK = 64;
constexpr int X_BYTES = BM * BK * 2;
constexpr int W_BYTES = BN * BK * 2;
constexpr int CHUNK_BYTES = BN * 16;
constexpr int OFF_X = 0;
constexpr int OFF_W = 3 * X_BYTES;
constexpr int OFF_STG = OFF_W + 3 * W_BYTES;
constexpr int OFF_LUT = OFF_W + 4 * W_BYTES;
constexpr int OFF_BAR = OFF_LUT + 7 * 2048;
constexpr int OFF_PROF = OFF_BAR + 1024;
constexpr int SMEM_BYTES = OFF_PROF + 1024 + 1024;
constexpr int B_FULL = 0;
constexpr int B_XV = 12;
constexpr int B_WF = 17;
constexpr int B_EMPTY = 22;
constexpr int B_DQ = 34;
constexpr int B_SLAB = 42;
constexpr int B_LUT = 46;

__device__ __align__(1024) uint4 g_w[(size_t)F_ * D_ / 8];
__device__ __align__(128) unsigned g_flags[16 * 32];

__device__ __forceinline__ uint32_t smem_u32(const void* p) { return (uint32_t)__cvta_generic_to_shared(p); }
__device__ __forceinline__ void mbar_init(uint32_t bar, uint32_t cnt) { asm volatile("mbarrier.init.shared::cta.b64 [%0], %1;" ::"r"(bar), "r"(cnt) : "memory"); }
__device__ __forceinline__ void mbar_wait(uint32_t bar) {
    asm volatile("{\n.reg .pred p;\nWAIT_LOOP:\nmbarrier.try_wait.parity.shared::cta.b64 p, [%0], 0;\n@p bra WAIT_DONE;\nbra WAIT_LOOP;\nWAIT_DONE:\n}" ::"r"(bar) : "memory");
}
__device__ __forceinline__ void e_arrive(uint32_t bar) {
    asm volatile("{\n.reg .pred p;\nelect.sync _|p, 0xffffffff;\n@p mbarrier.arrive.shared::cta.b64 _, [%0];\n}" ::"r"(bar) : "memory");
}
__device__ __forceinline__ void e_expect(uint32_t bar, uint32_t bytes) {
    asm volatile("{\n.reg .pred p;\nelect.sync _|p, 0xffffffff;\n@p mbarrier.arrive.expect_tx.shared::cta.b64 _, [%0], %1;\n}" ::"r"(bar), "r"(bytes) : "memory");
}
__device__ __forceinline__ void e_tma(uint32_t bar, const CUtensorMap* tm, uint32_t d0, int x0, int y0) {
    asm volatile("{\n.reg .pred p;\nelect.sync _|p, 0xffffffff;\n"
                 "@p cp.async.bulk.tensor.2d.shared::cluster.global.mbarrier::complete_tx::bytes [%2], [%1, {%3, %4}], [%0];\n}"
                 ::"r"(bar), "l"(tm), "r"(d0), "r"(x0), "r"(y0) : "memory");
}
__device__ __forceinline__ void e_bulk(uint32_t bar, uint32_t bytes, uint32_t dst, const void* src) {
    asm volatile("{\n.reg .pred p;\nelect.sync _|p, 0xffffffff;\n"
                 "@p mbarrier.arrive.expect_tx.shared::cta.b64 _, [%0], %1;\n"
                 "@p cp.async.bulk.shared::cluster.global.mbarrier::complete_tx::bytes [%2], [%3], %1, [%0];\n}"
                 ::"r"(bar), "r"(bytes), "r"(dst), "l"(src) : "memory");
}
__device__ __forceinline__ void e_bulk_p(uint32_t on, uint32_t bar, uint32_t bytes, uint32_t dst, const void* src) {
    if (on) asm volatile("{\n.reg .pred p;\nelect.sync _|p, 0xffffffff;\n"
                         "@p cp.async.bulk.shared::cluster.global.mbarrier::complete_tx::bytes [%2], [%3], %1, [%0];\n}"
                         ::"r"(bar), "r"(bytes), "r"(dst), "l"(src) : "memory");
}
__device__ __forceinline__ void e_prefetch2d(const CUtensorMap* tm, int x, int y) {
    asm volatile("{\n.reg .pred p;\nelect.sync _|p, 0xffffffff;\n@p cp.async.bulk.prefetch.tensor.2d.L2.global [%0, {%1, %2}];\n}" ::"l"(tm), "r"(x), "r"(y) : "memory");
}
#define FASTREL 0
__device__ __forceinline__ void e_publish(unsigned* flag) {
    asm volatile("{\n.reg .pred p;\nelect.sync _|p, 0xffffffff;\n@p red.release.gpu.global.add.u32 [%0], 1;\n}" ::"l"(flag) : "memory");
}
__device__ __forceinline__ void e_red(unsigned* flag, unsigned v) {
    asm volatile("{\n.reg .pred p;\nelect.sync _|p, 0xffffffff;\n@p red.relaxed.gpu.global.add.u32 [%0], %1;\n}" ::"l"(flag), "r"(v) : "memory");
}
__device__ __forceinline__ bool mbar_test(uint32_t bar) {
    uint32_t r;
    asm volatile("{\n.reg .pred p;\nmbarrier.test_wait.parity.shared::cta.b64 p, [%1], 0;\nselp.u32 %0, 1, 0, p;\n}" : "=r"(r) : "r"(bar) : "memory");
    return __all_sync(0xffffffff, r != 0);
}
template <int V> struct IC { static constexpr int value = V; };
__device__ __forceinline__ unsigned ld_flag(const unsigned* f) { unsigned v; asm volatile("ld.relaxed.gpu.global.u32 %0, [%1];" : "=r"(v) : "l"(f) : "memory"); return v; }
__device__ __forceinline__ void finish_poll(const unsigned* f, unsigned v, unsigned target) {
    int n = 0;
    while (!__all_sync(0xffffffff, (int)(v - target) >= 0) && ++n < 4000000) v = ld_flag(f);
    asm volatile("fence.acquire.gpu;" ::: "memory");
    asm volatile("fence.proxy.async.global;" ::: "memory");
}
template <typename T> __device__ __forceinline__ T* ptr_add(T* base, uint32_t off) {
    uint64_t r;
    asm("{\n.reg .u32 l, h;\nmov.b64 {l, h}, %1;\nadd.cc.u32 l, l, %2;\naddc.u32 h, h, 0;\nmov.b64 %0, {l, h};\n}" : "=l"(r) : "l"(base), "r"(off));
    return (T*)r;
}
__device__ __forceinline__ void wgmma_fence() { asm volatile("wgmma.fence.sync.aligned;" ::: "memory"); }
__device__ __forceinline__ void wgmma_commit() { asm volatile("wgmma.commit_group.sync.aligned;" ::: "memory"); }
template <int N> __device__ __forceinline__ void wgmma_wait() { asm volatile("wgmma.wait_group.sync.aligned %0;" ::"n"(N) : "memory"); }
__device__ __forceinline__ void wgmma_m64n224k16(float (&d)[112], uint64_t da, uint64_t db, int scale_d) {
    asm volatile(
        "{\n.reg .pred p;\nsetp.ne.b32 p, %114, 0;\n"
        "wgmma.mma_async.sync.aligned.m64n224k16.f32.bf16.bf16 "
        "{%0, %1, %2, %3, %4, %5, %6, %7, %8, %9, %10, %11, %12, %13, %14, %15, "
        "%16, %17, %18, %19, %20, %21, %22, %23, %24, %25, %26, %27, %28, %29, %30, %31, "
        "%32, %33, %34, %35, %36, %37, %38, %39, %40, %41, %42, %43, %44, %45, %46, %47, "
        "%48, %49, %50, %51, %52, %53, %54, %55, %56, %57, %58, %59, %60, %61, %62, %63, "
        "%64, %65, %66, %67, %68, %69, %70, %71, %72, %73, %74, %75, %76, %77, %78, %79, "
        "%80, %81, %82, %83, %84, %85, %86, %87, %88, %89, %90, %91, %92, %93, %94, %95, "
        "%96, %97, %98, %99, %100, %101, %102, %103, %104, %105, %106, %107, %108, %109, %110, %111}, "
        "%112, %113, p, 1, 1, 0, 0;\n}\n"
        : "+f"(d[0]), "+f"(d[1]), "+f"(d[2]), "+f"(d[3]), "+f"(d[4]), "+f"(d[5]), "+f"(d[6]), "+f"(d[7]),
          "+f"(d[8]), "+f"(d[9]), "+f"(d[10]), "+f"(d[11]), "+f"(d[12]), "+f"(d[13]), "+f"(d[14]), "+f"(d[15]),
          "+f"(d[16]), "+f"(d[17]), "+f"(d[18]), "+f"(d[19]), "+f"(d[20]), "+f"(d[21]), "+f"(d[22]), "+f"(d[23]),
          "+f"(d[24]), "+f"(d[25]), "+f"(d[26]), "+f"(d[27]), "+f"(d[28]), "+f"(d[29]), "+f"(d[30]), "+f"(d[31]),
          "+f"(d[32]), "+f"(d[33]), "+f"(d[34]), "+f"(d[35]), "+f"(d[36]), "+f"(d[37]), "+f"(d[38]), "+f"(d[39]),
          "+f"(d[40]), "+f"(d[41]), "+f"(d[42]), "+f"(d[43]), "+f"(d[44]), "+f"(d[45]), "+f"(d[46]), "+f"(d[47]),
          "+f"(d[48]), "+f"(d[49]), "+f"(d[50]), "+f"(d[51]), "+f"(d[52]), "+f"(d[53]), "+f"(d[54]), "+f"(d[55]),
          "+f"(d[56]), "+f"(d[57]), "+f"(d[58]), "+f"(d[59]), "+f"(d[60]), "+f"(d[61]), "+f"(d[62]), "+f"(d[63]),
          "+f"(d[64]), "+f"(d[65]), "+f"(d[66]), "+f"(d[67]), "+f"(d[68]), "+f"(d[69]), "+f"(d[70]), "+f"(d[71]),
          "+f"(d[72]), "+f"(d[73]), "+f"(d[74]), "+f"(d[75]), "+f"(d[76]), "+f"(d[77]), "+f"(d[78]), "+f"(d[79]),
          "+f"(d[80]), "+f"(d[81]), "+f"(d[82]), "+f"(d[83]), "+f"(d[84]), "+f"(d[85]), "+f"(d[86]), "+f"(d[87]),
          "+f"(d[88]), "+f"(d[89]), "+f"(d[90]), "+f"(d[91]), "+f"(d[92]), "+f"(d[93]), "+f"(d[94]), "+f"(d[95]),
          "+f"(d[96]), "+f"(d[97]), "+f"(d[98]), "+f"(d[99]), "+f"(d[100]), "+f"(d[101]), "+f"(d[102]), "+f"(d[103]),
          "+f"(d[104]), "+f"(d[105]), "+f"(d[106]), "+f"(d[107]), "+f"(d[108]), "+f"(d[109]), "+f"(d[110]), "+f"(d[111])
        : "l"(da), "l"(db), "r"(scale_d));
}

__device__ __forceinline__ void wgmma_rs_n32(float (&d)[16], const uint32_t* a, uint64_t db) {
    asm volatile("wgmma.mma_async.sync.aligned.m64n32k16.f32.bf16.bf16 {%0, %1, %2, %3, %4, %5, %6, %7, %8, %9, %10, %11, %12, %13, %14, %15}, {%16, %17, %18, %19}, %20, 1, 1, 1, 0;"
        : "+f"(d[0]), "+f"(d[1]), "+f"(d[2]), "+f"(d[3]), "+f"(d[4]), "+f"(d[5]), "+f"(d[6]), "+f"(d[7]), "+f"(d[8]), "+f"(d[9]), "+f"(d[10]), "+f"(d[11]), "+f"(d[12]), "+f"(d[13]), "+f"(d[14]), "+f"(d[15])
        : "r"(a[0]), "r"(a[1]), "r"(a[2]), "r"(a[3]), "l"(db));
}
__device__ __forceinline__ void wgmma_rs_n64(float (&d)[32], const uint32_t* a, uint64_t db) {
    asm volatile("wgmma.mma_async.sync.aligned.m64n64k16.f32.bf16.bf16 {%0, %1, %2, %3, %4, %5, %6, %7, %8, %9, %10, %11, %12, %13, %14, %15, %16, %17, %18, %19, %20, %21, %22, %23, %24, %25, %26, %27, %28, %29, %30, %31}, {%32, %33, %34, %35}, %36, 1, 1, 1, 0;"
        : "+f"(d[0]), "+f"(d[1]), "+f"(d[2]), "+f"(d[3]), "+f"(d[4]), "+f"(d[5]), "+f"(d[6]), "+f"(d[7]), "+f"(d[8]), "+f"(d[9]), "+f"(d[10]), "+f"(d[11]), "+f"(d[12]), "+f"(d[13]), "+f"(d[14]), "+f"(d[15]), "+f"(d[16]), "+f"(d[17]), "+f"(d[18]), "+f"(d[19]), "+f"(d[20]), "+f"(d[21]), "+f"(d[22]), "+f"(d[23]), "+f"(d[24]), "+f"(d[25]), "+f"(d[26]), "+f"(d[27]), "+f"(d[28]), "+f"(d[29]), "+f"(d[30]), "+f"(d[31])
        : "r"(a[0]), "r"(a[1]), "r"(a[2]), "r"(a[3]), "l"(db));
}
__device__ __forceinline__ void wgmma_rs_n128(float (&d)[64], const uint32_t* a, uint64_t db) {
    asm volatile("wgmma.mma_async.sync.aligned.m64n128k16.f32.bf16.bf16 {%0, %1, %2, %3, %4, %5, %6, %7, %8, %9, %10, %11, %12, %13, %14, %15, %16, %17, %18, %19, %20, %21, %22, %23, %24, %25, %26, %27, %28, %29, %30, %31, %32, %33, %34, %35, %36, %37, %38, %39, %40, %41, %42, %43, %44, %45, %46, %47, %48, %49, %50, %51, %52, %53, %54, %55, %56, %57, %58, %59, %60, %61, %62, %63}, {%64, %65, %66, %67}, %68, 1, 1, 1, 0;"
        : "+f"(d[0]), "+f"(d[1]), "+f"(d[2]), "+f"(d[3]), "+f"(d[4]), "+f"(d[5]), "+f"(d[6]), "+f"(d[7]), "+f"(d[8]), "+f"(d[9]), "+f"(d[10]), "+f"(d[11]), "+f"(d[12]), "+f"(d[13]), "+f"(d[14]), "+f"(d[15]), "+f"(d[16]), "+f"(d[17]), "+f"(d[18]), "+f"(d[19]), "+f"(d[20]), "+f"(d[21]), "+f"(d[22]), "+f"(d[23]), "+f"(d[24]), "+f"(d[25]), "+f"(d[26]), "+f"(d[27]), "+f"(d[28]), "+f"(d[29]), "+f"(d[30]), "+f"(d[31]), "+f"(d[32]), "+f"(d[33]), "+f"(d[34]), "+f"(d[35]), "+f"(d[36]), "+f"(d[37]), "+f"(d[38]), "+f"(d[39]), "+f"(d[40]), "+f"(d[41]), "+f"(d[42]), "+f"(d[43]), "+f"(d[44]), "+f"(d[45]), "+f"(d[46]), "+f"(d[47]), "+f"(d[48]), "+f"(d[49]), "+f"(d[50]), "+f"(d[51]), "+f"(d[52]), "+f"(d[53]), "+f"(d[54]), "+f"(d[55]), "+f"(d[56]), "+f"(d[57]), "+f"(d[58]), "+f"(d[59]), "+f"(d[60]), "+f"(d[61]), "+f"(d[62]), "+f"(d[63])
        : "r"(a[0]), "r"(a[1]), "r"(a[2]), "r"(a[3]), "l"(db));
}

__device__ __forceinline__ uint32_t pack_bf16(float lo, float hi) {
    uint32_t r; asm("cvt.rn.bf16x2.f32 %0, %1, %2;" : "=r"(r) : "f"(hi), "f"(lo)); return r;
}
__device__ __forceinline__ uint32_t lds32(uint32_t a) { uint32_t v; asm volatile("ld.shared.b32 %0, [%1];" : "=r"(v) : "r"(a)); return v; }
__device__ __forceinline__ void sts32(uint32_t a, uint32_t v) { asm volatile("st.shared.b32 [%0], %1;" ::"r"(a), "r"(v) : "memory"); }
__device__ __forceinline__ void sts128(uint32_t a, uint4 v) { asm volatile("st.shared.v4.b32 [%0], {%1,%2,%3,%4};" ::"r"(a), "r"(v.x), "r"(v.y), "r"(v.z), "r"(v.w) : "memory"); }
__device__ __forceinline__ void stg128(void* p, uint4 v) { asm volatile("st.global.v4.b32 [%0], {%1,%2,%3,%4};" ::"l"(p), "r"(v.x), "r"(v.y), "r"(v.z), "r"(v.w) : "memory"); }
__device__ __forceinline__ void cp16(uint32_t dst, const void* src) { asm volatile("cp.async.cg.shared.global [%0], [%1], 16;" ::"r"(dst), "l"(src) : "memory"); }
__device__ __forceinline__ void cp_commit() { asm volatile("cp.async.commit_group;" ::: "memory"); }
template <int N> __device__ __forceinline__ void cp_wait() { asm volatile("cp.async.wait_group %0;" ::"n"(N) : "memory"); }
__device__ __forceinline__ uint4 dequant8(uint32_t raw, uint32_t lut_a) {
    uint32_t v[8];
#pragma unroll
    for (int i = 0; i < 8; i++) v[i] = lds32(raw + i * 128);
#pragma unroll
    for (int i = 0; i < 8; i++) v[i] = lds32(lut_a + v[i] * 128);
    uint4 o;
    o.x = __byte_perm(v[0], v[1], 0x5410); o.y = __byte_perm(v[2], v[3], 0x5410);
    o.z = __byte_perm(v[4], v[5], 0x5410); o.w = __byte_perm(v[6], v[7], 0x5410);
    return o;
}
__device__ __forceinline__ uint32_t prmt(uint32_t a, uint32_t b, uint32_t c) { uint32_t r; asm("prmt.b32 %0, %1, %2, %3;" : "=r"(r) : "r"(a), "r"(b), "r"(c)); return r; }
__device__ __forceinline__ uint4 lookup8_reg(const uint32_t* c, const uint32_t (&T)[8], uint32_t two31) {
    uint32_t o[4];
#pragma unroll
    for (int h = 0; h < 2; h++) {
        const uint32_t sel = c[4 * h] + c[4 * h + 1] * 16 + c[4 * h + 2] * 256 + c[4 * h + 3] * 4096;
        const uint32_t s7 = sel & 0x7777u;
        uint32_t m;
        asm("lop3.b32 %0, %1, %2, 0x3210, 0xEA;" : "=r"(m) : "r"(__umulhi(sel, two31)), "r"(0x4444u));
        const uint32_t lo = prmt(prmt(T[0], T[1], s7), prmt(T[2], T[3], s7), m);
        const uint32_t hi = prmt(prmt(T[4], T[5], s7), prmt(T[6], T[7], s7), m);
        o[2 * h] = prmt(lo, hi, 0x5140u); o[2 * h + 1] = prmt(lo, hi, 0x7362u);
    }
    return make_uint4(o[0], o[1], o[2], o[3]);
}
template <int OFF, int G0, int G1, int N>
__device__ __forceinline__ void store_tile(const float (&acc)[N], __nv_bfloat16* o) {
#pragma unroll
    for (int G = G0; G < G1; G++) {
        uint4 v;
        v.x = pack_bf16(acc[G * 16 + 0], acc[G * 16 + 1]); v.y = pack_bf16(acc[G * 16 + 4], acc[G * 16 + 5]);
        v.z = pack_bf16(acc[G * 16 + 8], acc[G * 16 + 9]); v.w = pack_bf16(acc[G * 16 + 12], acc[G * 16 + 13]);
        stg128(o + OFF + G * 32, v);
        v.x = pack_bf16(acc[G * 16 + 2], acc[G * 16 + 3]); v.y = pack_bf16(acc[G * 16 + 6], acc[G * 16 + 7]);
        v.z = pack_bf16(acc[G * 16 + 10], acc[G * 16 + 11]); v.w = pack_bf16(acc[G * 16 + 14], acc[G * 16 + 15]);
        stg128(o + OFF + 8 * F_ + G * 32, v);
    }
}
template <int OFF, int N>
__device__ __forceinline__ void store_half(const float (&acc)[N], __nv_bfloat16* o, int H, int on = 1) {
    const int b = (H >> 1) * 16 + (H & 1) * 2;
    uint4 v;
    v.x = pack_bf16(acc[b + 0], acc[b + 1]); v.y = pack_bf16(acc[b + 4], acc[b + 5]);
    v.z = pack_bf16(acc[b + 8], acc[b + 9]); v.w = pack_bf16(acc[b + 12], acc[b + 13]);
    asm volatile("{\n.reg .pred p;\nsetp.ne.b32 p, %5, 0;\n@p st.global.v4.b32 [%0], {%1,%2,%3,%4};\n}"
                 ::"l"(o + OFF + (H & 1) * 8 * F_ + (H >> 1) * 32), "r"(v.x), "r"(v.y), "r"(v.z), "r"(v.w), "r"(on) : "memory");
}
template <int N>
__device__ __forceinline__ void pack_half(const float (&acc)[N], int H, uint32_t* r) {
    const int b = (H >> 1) * 16 + (H & 1) * 2;
#pragma unroll
    for (int i = 0; i < 4; i++) asm volatile("cvt.rn.bf16x2.f32 %0, %1, %2;" : "=r"(r[i]) : "f"(acc[b + 4 * i + 1]), "f"(acc[b + 4 * i]));
}
__device__ __forceinline__ void store_packed(__nv_bfloat16* o, int H, const uint32_t* r, int on) {
    asm volatile("{\n.reg .pred p;\nsetp.ne.b32 p, %5, 0;\n@p st.global.v4.b32 [%0], {%1,%2,%3,%4};\n}"
                 ::"l"(o + (H & 1) * 8 * F_ + (H >> 1) * 32), "r"(r[0]), "r"(r[1]), "r"(r[2]), "r"(r[3]), "r"(on) : "memory");
}
constexpr int NROUNDS = 8;
constexpr unsigned long long R_FIRST = 0xFDB97543ull, R_BATCH = 0x60050400ull, R_DOUBLE = 0x7C;
constexpr unsigned long long W_FLAG = 0x600504000ull;
constexpr unsigned L1_MASK = W4L2 ? 0x2A : 0x2E, L2_MASK = W4L2 ? 0x1EA : 0x1E8; constexpr int W12_AT = 8;
constexpr int NFAST = NF;
__device__ __forceinline__ int round_first(int r) { return (int)(R_FIRST >> (4 * r)) & 15; }
__device__ __forceinline__ int round_batch(int r) { return (int)(R_BATCH >> (4 * r)) & 15; }

#define TSK(w, i)
#define TSF(i)
#define TSP(i)
#define TSQ(i)
#define PW 0
#define TS8(i)
#define TSW(w, i)

template <bool HARD>
__global__ void __launch_bounds__(256, 1)
fused_kernel(const int* __restrict__ qw, const unsigned short* __restrict__ lut, __nv_bfloat16* __restrict__ out,
             uint4* __restrict__ wscr, unsigned* __restrict__ flags, const uint32_t two31,
             const __grid_constant__ CUtensorMap tmq, const __grid_constant__ CUtensorMap tmx64, const __grid_constant__ CUtensorMap tmx
) {
    extern __shared__ uint8_t smem_raw[];
    const uint32_t sbase = HARD ? 1024u : (smem_u32(smem_raw) + 1023) & ~1023u;
    const uint32_t bars = sbase + OFF_BAR;
    const int tid = threadIdx.x, lane = tid & 31;
    const int mt = blockIdx.x & 7, g = blockIdx.x >> 3;
    unsigned clk0; asm volatile("mov.u32 %0, %%clock;" : "=r"(clk0));
    constexpr int SLAB_BYTES = 16 * BN * 4, OFF_SLAB0 = OFF_W + 2 * W_BYTES, OFF_SLAB2 = OFF_X + 2 * X_BYTES;
    const int warp = __shfl_sync(0xffffffff, tid >> 5, 0);
    if (tid >= 224) {
        asm volatile("{\n.reg .pred p;\nelect.sync _|p, 0xffffffff;\n"
                     "@p mbarrier.init.shared::cta.b64 [%0], 1;\n"
                     "@p fence.mbarrier_init.release.cluster;\n"
                     "@p mbarrier.arrive.expect_tx.shared::cta.b64 _, [%0], %1;\n"
                     "@p cp.async.bulk.tensor.2d.shared::cluster.global.mbarrier::complete_tx::bytes [%3], [%2, {%4, 0}], [%0];\n}"
                     ::"r"(bars + 8 * B_SLAB), "n"(SLAB_BYTES), "l"(&tmq), "r"(sbase + OFF_SLAB0), "r"(g * BN) : "memory");
    } else {
        const unsigned short* lp = ptr_add(lut, ((lane >> 2) * F_ + g * BN + (tid & ~31) + (lane & 3) * 8) * 2);
        asm volatile("cp.async.cg.shared.global [%0], [%1], 16;\ncp.async.cg.shared.global [%0+512], [%1+57344], 16;\ncp.async.commit_group;"
                     ::"r"(sbase + OFF_STG + (tid >> 5) * 4096 + lane * 16), "l"(lp) : "memory");
    }
    const int sl = warp - 3;
    auto load_slab = [&]() {
        e_tma(bars + 8 * (B_SLAB + sl), &tmq, sbase + (sl < 2 ? OFF_SLAB0 : OFF_SLAB2 - 2 * SLAB_BYTES) + sl * SLAB_BYTES, g * BN, sl * 16);
    };
    if (warp >= 4 && warp < 7) {
        asm volatile("{\n.reg .pred p;\nelect.sync _|p, 0xffffffff;\n"
                     "@p mbarrier.init.shared::cta.b64 [%0], 1;\n"
                     "@p fence.mbarrier_init.release.cluster;\n"
                     "@p mbarrier.arrive.expect_tx.shared::cta.b64 _, [%0], %1;\n}"
                     ::"r"(bars + 8 * (B_SLAB + sl)), "n"(SLAB_BYTES) : "memory");
        if (sl < NOW) load_slab();
    } else if (warp < 2) {
        asm volatile("{\n.reg .pred p;\nelect.sync _|p, 0xffffffff;\n"
                     "@p mbarrier.init.shared::cta.b64 [%0], %1;\n"
                     "@p fence.mbarrier_init.release.cluster;\n}" ::"r"(bars + 8 * (warp ? B_LUT : B_FULL)), "r"(8 - warp) : "memory");
    }
    asm volatile("bar.sync 1, 256;" ::: "memory");
    TSQ(0);
    const int wg = warp >> 2;

    const int fl = 8 * ((lane & 7) >> 1) + 2 * (lane >> 3) + (lane & 1);
    const uint32_t lut_a = sbase + OFF_LUT + warp * 2048 + lane * 4;
    const uint32_t stg = sbase + OFF_STG + warp * 4096;
    unsigned* myflags = flags + g * 32;
    const uint4* wgrp = wscr + (size_t)g * 128 * BN;
    unsigned target = 0;

    auto issue_x = [&](int s, int slot) {
        e_tma(bars + 8 * (B_FULL + s), &tmx, sbase + OFF_X + slot * X_BYTES, s * BK, mt * BM);
    };
    auto pf_x = [&](int s, int row0) { e_prefetch2d(&tmx64, s * BK, row0); };
    auto issue_xv = [&](int v, int w, uint32_t bar) {
        const uint32_t dst = sbase + OFF_X + (v & 1) * X_BYTES + w * 16384;
        const int k0 = (12 + 2 * (v & 1)) * BK, r0 = mt * BM + w * 128 + ((v >> 1) & 1) * 64;
        e_tma(bar, &tmx64, dst, k0, r0);
        e_tma(bar, &tmx64, dst + 8192, k0 + BK, r0);
    };
    auto issue_w = [&](int s, int slot, int bar) {
        e_bulk(bars + 8 * bar, W_BYTES, sbase + OFF_W + slot * W_BYTES, wgrp + s * 8 * BN);
    };
    auto load_raw = [&](int t) {
        if (t < 16) {
            const int* src = ptr_add(qw, (uint32_t)(((t * BK + mt * 8 + (lane >> 3)) * F_ + g * BN + warp * 32 + (lane & 7) * 4) * 4));
            asm volatile("cp.async.cg.shared.global [%0], [%1], 16;\ncp.async.cg.shared.global [%0+512], [%1+57344], 16;"
                         ::"r"(stg + (t & 3) * 1024 + lane * 16), "l"(src) : "memory");
        }
        cp_commit();
    };
    auto load_blk = [&](int t, int c) {
        const int* src = ptr_add(qw, (uint32_t)(((t * BK + mt * 8 + (lane >> 3)) * F_ + g * BN + c * 32 + (lane & 7) * 4) * 4));
        asm volatile("cp.async.cg.shared.global [%0], [%1], 16;\ncp.async.cg.shared.global [%0+512], [%1+57344], 16;"
                     ::"r"(sbase + OFF_STG + c * 4096 + t * 1024 + lane * 16), "l"(src) : "memory");
    };
    auto foreign = [&](int t) {
        const int c = warp ^ 4;
        stg128(ptr_add(wscr, (uint32_t)(((g * 128 + t * 8 + mt) * BN + c * 32 + lane) * 16)),
               dequant8(sbase + OFF_STG + c * 4096 + t * 1024 + fl * 4, sbase + OFF_LUT + c * 2048 + lane * 4));
        TSW(4, 5);
    };
    auto my_unit = [&](int t) { return ptr_add(wscr, (uint32_t)(((g * 128 + t * 8 + mt) * BN + warp * 32 + lane) * 16)); };
    auto coop = [&](int t) {
        cp_wait<LA - 1>();
        __syncwarp();
        load_raw(t + LA);
        stg128(my_unit(t), dequant8(stg + (t & 3) * 1024 + fl * 4, lut_a));

    };
    auto coop2 = [&](int t) {
        cp_wait<0>();
        __syncwarp();
        if (t < 14) {
            const int* src = ptr_add(qw, (uint32_t)((((t + 2) * BK + mt * 8 + (lane >> 3)) * F_ + g * BN + warp * 32 + (lane & 7) * 4) * 4));
            asm volatile("cp.async.cg.shared.global [%0], [%1], 16;\ncp.async.cg.shared.global [%0+512], [%1+57344], 16;"
                         ::"r"(stg + ((t + 2) & 3) * 1024 + lane * 16), "l"(src) : "memory");
            if (t < 13) asm volatile("cp.async.cg.shared.global [%0], [%1+917504], 16;\ncp.async.cg.shared.global [%0+512], [%1+974848], 16;"
                                     ::"r"(stg + ((t + 3) & 3) * 1024 + lane * 16), "l"(src) : "memory");
            cp_commit();
        }
        uint32_t v[16];
        const uint32_t r0 = stg + (t & 3) * 1024 + fl * 4, r1 = stg + ((t + 1) & 3) * 1024 + fl * 4;
#pragma unroll
        for (int i = 0; i < 8; i++) v[i] = lds32(r0 + i * 128);
#pragma unroll
        for (int i = 0; i < 8; i++) v[8 + i] = lds32(r1 + i * 128);
#pragma unroll
        for (int i = 0; i < 16; i++) v[i] = lds32(lut_a + v[i] * 128);
        uint4* dst = my_unit(t);
        stg128(dst, make_uint4(prmt(v[0], v[1], 0x5410), prmt(v[2], v[3], 0x5410), prmt(v[4], v[5], 0x5410), prmt(v[6], v[7], 0x5410)));
        if (t < 15) stg128(dst + 8 * BN, make_uint4(prmt(v[8], v[9], 0x5410), prmt(v[10], v[11], 0x5410), prmt(v[12], v[13], 0x5410), prmt(v[14], v[15], 0x5410)));
    };
    auto pace = [&](unsigned t) { unsigned c; do { asm volatile("mov.u32 %0, %%clock;" : "=r"(c)); } while (c - clk0 < t); };
    if (warp == 7) {
        TSW(7, 2); TSQ(1);
        if (lane == 0) {
            asm volatile("prefetch.tensormap [%0];" ::"l"(&tmx) : "memory");
            asm volatile("prefetch.tensormap [%0];" ::"l"(&tmx64) : "memory");
        }
        __syncwarp();
        TSW(7, 13); TSQ(3);
        pace(PX0);
        e_expect(bars + 8 * B_FULL, X_BYTES);
        issue_x(0, 0);
        TSQ(4);
        if (R1MODE == 4) {
            pace(PR1);
#pragma unroll
            for (int c = 0; c < 4; c++) load_blk(1, c);
            cp_commit();
        }
        target = ld_flag(myflags + 6);
        TSW(7, 1);
        pace(PR2);
        load_blk(2, 3);
        cp_commit();
        mbar_wait(bars + 8 * B_LUT);
        if (R1MODE == 4) {
            uint32_t c[32];
            cp_wait<1>();
            __syncwarp();
#pragma unroll
            for (int i = 0; i < 32; i++) c[i] = lds32(sbase + OFF_STG + (i >> 3) * 4096 + 1024 + (i & 7) * 128 + fl * 4);
#pragma unroll
            for (int i = 0; i < 32; i++) c[i] = lds32(sbase + OFF_LUT + (i >> 3) * 2048 + lane * 4 + c[i] * 128);
            uint4* dst = ptr_add(wscr, (uint32_t)(((g * 128 + 8 + mt) * BN + lane) * 16));
#pragma unroll
            for (int b = 0; b < 4; b++)
                stg128(dst + b * 32, make_uint4(prmt(c[8 * b], c[8 * b + 1], 0x5410), prmt(c[8 * b + 2], c[8 * b + 3], 0x5410),
                                                prmt(c[8 * b + 4], c[8 * b + 5], 0x5410), prmt(c[8 * b + 6], c[8 * b + 7], 0x5410)));
            TSW(7, 14);
        }
        target = (target | 7) + 1;
        if (PFX > 100) { pace(PFX); pf_x(PFXB + (g >> 2), mt * BM + (g & 3) * 64); }
        if (PX1 < 100000) { pace(PX1); issue_x(1, 1); }
        if (F2POS == 0) { cp_wait<0>(); __syncwarp(); foreign(2); }
        mbar_wait(bars + 8 * B_FULL);
        if (PX1 == 100000) issue_x(1, 1);
        if (PFX == 1) pf_x(PFXB + (g >> 2), mt * BM + (g & 3) * 64);
        if (F2POS == 1) { cp_wait<0>(); __syncwarp(); foreign(2); }
        if (W1BY == 7) {
            if (W1D) { unsigned c, c0; asm volatile("mov.u32 %0, %%clock;" : "=r"(c0)); do { asm volatile("mov.u32 %0, %%clock;" : "=r"(c)); } while (c - c0 < W1D); }
            e_bulk_p(1, bars + 8 * (B_FULL + 1), W_BYTES, sbase + OFF_W + W_BYTES, wgrp + 8 * BN);
            TSW(7, 4);
        }
        if (PX1 == 100001) issue_x(1, 1);
        if (F2POS == 2) { cp_wait<0>(); __syncwarp(); foreign(2); }
        if (PFX == 2) pf_x(PFXB + (g >> 2), mt * BM + (g & 3) * 64);
        TSW(7, 3);
    } else {
        if (wg == 1 && sl >= NOW) { pace(PSBASE + sl * PSTEP); load_slab(); }
        auto init_bars = [&]() {
            if (lane == 0) {
#pragma unroll
                for (int i = 0; i < 6; i++) {
                    const int b = 1 + warp * 6 + i;
                    if (b < B_SLAB) mbar_init(bars + 8 * b, b < B_DQ ? 1 : 7);
                    if (b < B_XV) asm volatile("mbarrier.arrive.expect_tx.shared::cta.b64 _, [%0], %1;" ::"r"(bars + 8 * b), "r"(X_BYTES + W_BYTES) : "memory");
                }
                asm volatile("fence.mbarrier_init.release.cluster;" ::: "memory");
            }
            __syncwarp();
        };
        init_bars();
        if (R1MODE != 4 || wg == 1) { pace(PR1); load_blk(1, warp); }
        cp_commit();
        TSW(0, 15);
        uint32_t lv[16], v[32], T[8];
        cp_wait<1>();
        __syncwarp();
#pragma unroll
        for (int i = 0; i < 16; i++) asm volatile("ld.shared.u16 %0, [%1];" : "=r"(lv[i]) : "r"(stg + i * 64 + fl * 2));
#pragma unroll
        for (int i = 0; i < 16; i++) lv[i] = lv[i] ? lv[i] : 0x8000u;
#pragma unroll
        for (int i = 0; i < 4; i++) {
            const uint32_t p01 = prmt(lv[4 * i], lv[4 * i + 1], 0x5140u), p23 = prmt(lv[4 * i + 2], lv[4 * i + 3], 0x5140u);
            T[i] = prmt(p01, p23, 0x5410u); T[4 + i] = prmt(p01, p23, 0x7632u);
        }
        TSW(0, 7);
#pragma unroll
        for (int i = 0; i < 16; i++) sts32(lut_a + i * 128, lv[i]);
        __syncwarp();
        e_arrive(bars + 8 * B_LUT);
        auto more_raw = [&](int j) {
            if (R2AT == j && wg == 1) { load_blk(2, warp); load_blk(2, warp - 4); cp_commit(); }
            if (R3AT == j && wg == 0) load_raw(3);
            if (R3W1 == j && wg == 1) load_raw(3);
        };
        auto own_task = [&](int t) {
            __syncwarp();
            uint32_t c[8];
#pragma unroll
            for (int i = 0; i < 8; i++) c[i] = lds32(stg + t * 1024 + fl * 4 + i * 128);
            uint4 o = lookup8_reg(c, T, two31);
            stg128(my_unit(t), o);
            if (t == 1) { TSW(4, 6); if (R1MODE != 4) TSW(0, 14); }
        };
        auto raw1_task = [&]() {
            if (wg == 1) cp_wait<(R2AT < 4) + (R3W1 < 4)>(); else cp_wait<(R3AT < 4)>();
            own_task(1);
        };
        auto piece_ld = [&](int j) {
            TSP(j * 8);
            mbar_wait(bars + 8 * (B_SLAB + j));
            TSP(j * 8 + 1);
#pragma unroll
            for (int i = 0; i < 16; i++) v[(j & 1) * 16 + i] = lds32(sbase + (j < 2 ? OFF_SLAB0 : OFF_SLAB2) + (j & 1) * SLAB_BYTES + i * (BN * 4) + (warp * 32 + fl) * 4);
            more_raw(j);
        };
        auto piece_st = [&](int j) {
            const uint32_t dst = sbase + OFF_W + j * 2 * CHUNK_BYTES + (warp * 32 + lane) * 16;
            sts128(dst, lookup8_reg(v + (j & 1) * 16, T, two31));
            sts128(dst + CHUNK_BYTES, lookup8_reg(v + (j & 1) * 16 + 8, T, two31));
            TSP(j * 8 + 2);
            TSW(PW, 8 + j);
        };
        if (R2AT < 0 && wg == 1) { pace(PR2); more_raw(R2AT); }
        piece_ld(0);
        if (PIPE & 1) piece_ld(1);
        piece_st(0);
        if (!(PIPE & 1)) piece_ld(1);
        if (PIPE & 2) piece_ld(2);
        piece_st(1);
        if (!(PIPE & 2)) piece_ld(2);
        if (PIPE & 4) piece_ld(3);
        piece_st(2);
        if (!(PIPE & 4)) piece_ld(3);
        if (R1MODE == 2 || (R1MODE == 3 && wg == 0)) raw1_task();
        piece_st(3);
        asm volatile("fence.proxy.async.shared::cta;" ::: "memory");
        TSP(27);
        __syncwarp();
        e_arrive(bars + 8 * B_FULL);
        if (R1MODE == 1 || (wg == 1 && R1MODE >= 3)) raw1_task();
        more_raw(4);
        if (wg == 1) {
            cp_wait<(R3W1 < 5)>();
            own_task(2);
            if (R34AT == 0) { if (R3W1 == 5) load_raw(3); load_raw(4); }
            mbar_wait(bars + 8 * B_LUT);
            foreign(2);
            if (R34AT == 1) { if (R3W1 == 5) load_raw(3); load_raw(4); }
        }
        TSW(4, 12);
    }

    float acc0[112], acc1[112];
    const uint64_t descA_hi = ((uint64_t)1 << 62) | ((uint64_t)(1024 >> 4) << 32) | ((uint64_t)1 << 16);
    const uint64_t descB_hi = ((uint64_t)(128 >> 4) << 32) | ((uint64_t)(CHUNK_BYTES >> 4) << 16);
    const uint32_t a16 = ((sbase & 0x3FFFF) >> 4) + wg * 1024 + (uint32_t)descA_hi, b16w = (((sbase + OFF_W) & 0x3FFFF) >> 4) + (uint32_t)descB_hi;
    auto dscA = [&](uint32_t lo) { return (descA_hi & 0xFFFFFFFF00000000ull) | lo; };
    auto dscB = [&](uint32_t lo) { return (descB_hi & 0xFFFFFFFF00000000ull) | lo; };
    uint32_t xo = 0, wo = 0, wo_prev = 2 * W_BYTES;
    const uint4* wnext = wgrp + 2 * 8 * BN;
    auto validate = [&](int t, uint32_t wofs) {
        constexpr int NV = VSPLIT == 1 ? 7 : 14;
        const uint32_t u = VSPLIT == 1 ? tid + wg * (W_BYTES / 32 - 128) : tid & 127;
        const uint32_t a = sbase + OFF_W + wofs + u * 16;
        for (int n = 0; n < 2000000; n++) {
            uint32_t m = 0xffffffffu;
#pragma unroll
            for (int i = 0; i < 7; i++) m = min(m, lds32(a + u * 16 + (lane >> 2) * 4 + i * 4096));
            if (__all_sync(0xffffffff, m != 0)) break;
            const uint4* src = ptr_add(wgrp, (uint32_t)((t * 8 * BN + (u & ~31) * 2 + lane) * 16));
#pragma unroll 1
            for (int i = 0; i < 14; i++) cp16(sbase + OFF_W + wofs + ((u & ~31) * 2 + lane + (i >> 1) * 256 + (i & 1) * 32) * 16, src + (i >> 1) * 256 + (i & 1) * 32);
            cp_commit();
            cp_wait<0>();
            asm volatile("fence.proxy.async.shared::cta;" ::: "memory");
            __syncwarp();
        }
    };
    auto batch = [&](int s, bool val) {
        if (val && s == 0) TSP(28);
        mbar_wait(bars + 8 * (B_FULL + s));
        if (val && s == 0) TSP(29);
        if (val && VSPLIT != 2 && wg == 0 && (unsigned)(s - 1) < NFAST) validate(s, wo);
        if (s + wg > 0) asm volatile("bar.sync %0, 256;" ::"r"(2 + wg) : "memory");
        TSW(0, 16 + s); TSW(4, 48 + s); TS8(16 + s);
        const uint32_t al = a16 + (xo >> 4), bl = b16w + (wo >> 4);
        wgmma_fence();
#pragma unroll
        for (int kk = 0; kk < 4; kk++) {
            const uint64_t db = dscB(bl + kk * (2 * CHUNK_BYTES >> 4));
            wgmma_m64n224k16(acc0, dscA(al + kk * 2), db, (s | kk) != 0);
            wgmma_m64n224k16(acc1, dscA(al + kk * 2 + (8192 >> 4)), db, (s | kk) != 0);
        }
        wgmma_commit();
        if (val && VSPLIT && wg == 1 && s < NFAST) { mbar_wait(bars + 8 * (B_FULL + s + 1)); validate(s + 1, 3 * W_BYTES - wo - wo_prev); }
        asm volatile("bar.arrive %0, 256;" ::"r"(3 - wg) : "memory");
        TSW(0, 32 + s); TSW(4, 64 + s);
    };
    auto advance = [&]() {
        wo_prev = wo;
        xo = xo == 2 * X_BYTES ? 0 : xo + X_BYTES;
        wo = wo == 2 * W_BYTES ? 0 : wo + W_BYTES;
        wnext += 8 * BN;
    };
    if (PEEL) batch(0, false);
#pragma unroll 1
    for (int s = 0; s < 9; s++) {
        if (!PEEL) batch(s, true);
        const uint32_t bs = bars + 8 * s;
        if (warp == 7) {
            const int fb = (int)(W_FLAG >> (4 * s)) & 15;
            unsigned* fp = ptr_add(myflags, fb * 4);
            unsigned fv = target;
            const int pb = round_batch(s);
            const uint32_t l1 = (L1_MASK >> s) & 1, l2 = (L2_MASK >> s) & 1;
            if (fb) fv = ld_flag(fp);
            else e_bulk_p(l1 && !pb, bs + 8 * (B_FULL + 2), W_BYTES, sbase + OFF_W + wo_prev, wnext);
            if (s == 0) {
                if (X2POS == 0) issue_x(2, 2);
                if (PFX == 3) pf_x(PFXB + (g >> 2), mt * BM + (g & 3) * 64);
                if (W2POS == 0) {
                    if (W2D) { unsigned c, c0; asm volatile("mov.u32 %0, %%clock;" : "=r"(c0)); do { asm volatile("mov.u32 %0, %%clock;" : "=r"(c)); } while (c - c0 < W2D); }
                    e_bulk_p(1, bs + 8 * (B_FULL + 2), W_BYTES, sbase + OFF_W + wo_prev, wnext);
                }
            }
            TSW(7, 112 + s);
            if (s == 0 && X2POS == 1) issue_x(2, 2);
            if (pb) {
                mbar_wait(bars + 8 * (B_DQ + pb));
                mbar_wait(bs + 8 * B_EMPTY);
                e_publish(ptr_add(myflags, pb * 4));
                e_bulk_p(l1, bs + 8 * (B_FULL + 2), W_BYTES, sbase + OFF_W + wo_prev, wnext);
            } else {
                if (fb) {
                    finish_poll(fp, fv, target);
                    e_bulk_p(l1, bs + 8 * (B_FULL + 2), W_BYTES, sbase + OFF_W + wo_prev, wnext);
                }
                mbar_wait(bs + 8 * B_EMPTY);
                if (s == W12_AT) {
                    issue_w(12, 3, B_WF);
                    e_bulk(bars + 8 * (B_WF + 3), W_BYTES / 2, sbase + OFF_LUT, wgrp + 15 * 8 * BN);
                }
            }
            wgmma_wait<0>();
            if (W2POS == 1) e_bulk_p(s == 0, bs + 8 * (B_FULL + 2), W_BYTES, sbase + OFF_W + wo_prev, wnext);
            e_bulk_p(l2, bs + 8 * (B_FULL + 3), W_BYTES, sbase + OFF_W + wo, wnext + 8 * BN);
            e_tma(bs + 8 * (B_FULL + 3), &tmx, sbase + OFF_X + xo, (s + 3) * BK, mt * BM);
            TSW(7, 96 + s);
        } else {
            if (s == 0) {
                if (wg == 0) {
                    if (R3AT > 4) load_raw(3);
                    if (R4W0 == 0) load_raw(4);
                    if (warp == W1BY) {
                        if (W1D) { unsigned c, c0; asm volatile("mov.u32 %0, %%clock;" : "=r"(c0)); do { asm volatile("mov.u32 %0, %%clock;" : "=r"(c)); } while (c - c0 < W1D); }
                        e_bulk_p(1, bars + 8 * (B_FULL + 1), W_BYTES, sbase + OFF_W + W_BYTES, wgrp + 8 * BN); TSW(3, 4);
                    }
                } else if (R34AT == 2) { if (R3W1 == 5) load_raw(3); load_raw(4); }
            }
            const int r = s + wg;
            if (R4W0 && r == 0) {
                cp_wait<0>();
                __syncwarp();
                stg128(my_unit(3), dequant8(stg + 3 * 1024 + fl * 4, lut_a));
                if (R4W0 == 2) mbar_wait(bars + 8 * (B_FULL + 1));
                load_raw(4); load_raw(5);
            } else if (wg == 0 && s < 2) coop(s + 3);
            else if (r < NROUNDS) { if (PAIR) coop2(2 * r + 1); else { coop(2 * r + 1); if (r < 7) coop(2 * r + 2); } }
            if (round_batch(r)) { __syncwarp(); e_arrive(bars + 8 * (B_DQ + round_batch(r))); }
            TSW(0, 80 + s);
            wgmma_wait<0>();
            if (warp == 3) e_arrive(bs + 8 * B_EMPTY);
            if (warp == 2 && (s & 3) == 1) pf_x(s + 4 + (g >> 2), mt * BM + (g & 3) * 64);
        }
        advance();
        if (PEEL) batch(s + 1, true);
    }
    auto rezero = [&]() {
        mbar_wait(bars + 8 * (B_FULL + 11));
#pragma unroll
        for (int t = 1; t <= NFAST; t++) stg128(my_unit(t), make_uint4(0, 0, 0, 0));
    };
    {
        if (!PEEL) batch(9, false);
        if (warp == 7) {
            pf_x(13 + (g >> 2), mt * BM + (g & 3) * 64);
            mbar_wait(bars + 8 * (B_EMPTY + 9));
        } else if (ZPOS == 9) rezero();
        wgmma_wait<0>();
        if (warp == 3) e_arrive(bars + 8 * (B_EMPTY + 9));
        if (warp == 7) {
            issue_w(13, 0, B_WF + 1);
            e_expect(bars + 8 * B_XV, X_BYTES);
            issue_xv(12, 0, bars + 8 * B_XV); issue_xv(12, 1, bars + 8 * B_XV);
        }
        advance();
        batch(10, false);
        if (warp == 7) mbar_wait(bars + 8 * (B_EMPTY + 10)); else if (ZPOS == 10) rezero();
        wgmma_wait<0>();
        if (warp == 3) e_arrive(bars + 8 * (B_EMPTY + 10));
    }
    const int w4 = warp & 3;
    __nv_bfloat16* o = ptr_add(out, (uint32_t)(((mt * BM + wg * 128 + w4 * 16 + (lane >> 2)) * F_ + g * BN + (lane & 3) * 8) * 2));
    auto wofs = [](int st, int kk) -> uint32_t {
        return st < 15 ? OFF_W + (st == 11 ? 2 : st == 12 ? 3 : st - 13) * W_BYTES + kk * 2 * CHUNK_BYTES
                       : kk < 2 ? OFF_LUT + kk * 2 * CHUNK_BYTES : OFF_X + 2 * X_BYTES + (kk - 2) * 16384;
    };
    auto xofs = [](int st, int kk, int r) -> uint32_t {
        return (st == 11 ? 2 * X_BYTES + r * 8192 : ((st - 12) >> 1) * X_BYTES + (st & 1) * 8192) + kk * 32;
    };
    auto launder = [&]() { uint32_t b16 = (sbase & 0x3FFFF) >> 4; asm volatile("mov.u32 %0, %0;" : "+r"(b16)); return b16; };
    auto dA = [&](uint32_t b16, uint32_t ofs) { return (descA_hi & 0xFFFFFFFF00000000ull) | (uint64_t)(b16 + wg * 1024 + (ofs >> 4) + (uint32_t)descA_hi); };
    auto dB = [&](uint32_t b16, uint32_t ofs) { return (descB_hi & 0xFFFFFFFF00000000ull) | (uint64_t)(b16 + (ofs >> 4) + (uint32_t)descB_hi); };
    float p0[64], p1[32], p2[16];
    constexpr int PK0 = ASP < CSP ? ASP : CSP;
    uint32_t pk[(14 - PK0) * 4 + 1];
    {
        mbar_wait(bars + 8 * (B_FULL + 11));
        asm volatile("bar.sync %0, 256;" ::"r"(2 + wg) : "memory");
        const uint32_t b16 = launder();
        wgmma_fence();
#pragma unroll
        for (int kk = 0; kk < 4; kk++) wgmma_m64n224k16(acc0, dA(b16, xofs(11, kk, 0)), dB(b16, wofs(11, kk)), 1);
        wgmma_commit();
        asm volatile("bar.arrive %0, 256;" ::"r"(3 - wg) : "memory");
        if (warp == 7) {
            issue_w(14, 1, B_WF + 2);
            e_expect(bars + 8 * (B_XV + 1), X_BYTES);
            issue_xv(13, 0, bars + 8 * (B_XV + 1)); issue_xv(13, 1, bars + 8 * (B_XV + 1));
            mbar_wait(bars + 8 * (B_EMPTY + 11));
        } else if (ZPOS == 11) rezero();
        if (FADDPOS == 0) {
#pragma unroll
            for (int i = 0; i < 64; i++) asm volatile("add.f32 %0, %1, 0f00000000;" : "=f"(p0[i]) : "f"(acc1[i]));
#pragma unroll
            for (int i = 0; i < 32; i++) asm volatile("add.f32 %0, %1, 0f00000000;" : "=f"(p1[i]) : "f"(acc1[64 + i]));
#pragma unroll
            for (int i = 0; i < 16; i++) asm volatile("add.f32 %0, %1, 0f00000000;" : "=f"(p2[i]) : "f"(acc1[96 + i]));
        }
        wgmma_wait<0>();
        if (warp == 3) e_arrive(bars + 8 * (B_EMPTY + 11));
        if (warp == 7) {
            e_bulk(bars + 8 * (B_WF + 4), 2 * CHUNK_BYTES, sbase + wofs(15, 2), wgrp + (15 * 8 + 4) * BN);
            e_bulk(bars + 8 * (B_XV + 4), 2 * CHUNK_BYTES, sbase + wofs(15, 3), wgrp + (15 * 8 + 6) * BN);
        }
    }
    {
        asm volatile("bar.sync %0, 256;" ::"r"(2 + wg) : "memory");
        TSK(0, 28); TSF(0);
        const uint32_t b16 = launder();
#pragma unroll
        for (int st = 12; st < 16; st++) {
            if (!(st & 1)) mbar_wait(bars + 8 * (B_XV + ((st - 12) >> 1)));
            mbar_wait(bars + 8 * (B_WF + st - 12));
            if (!(st & 1)) wgmma_fence();
#pragma unroll
            for (int kk = 0; kk < 4; kk++) {
                if (st == 15 && kk >= 2) mbar_wait(bars + 8 * (kk == 2 ? B_WF + 4 : B_XV + 4));
                wgmma_m64n224k16(acc0, dA(b16, xofs(st, kk, 0)), dB(b16, wofs(st, kk)), 1);
            }
            if (st & 1) wgmma_commit();
        }
        asm volatile("bar.arrive %0, 256;" ::"r"(3 - wg) : "memory");
        TSF(1);
        if (FADDPOS == 1) {
#pragma unroll
            for (int i = 0; i < 64; i++) asm volatile("add.f32 %0, %1, 0f00000000;" : "=f"(p0[i]) : "f"(acc1[i]));
#pragma unroll
            for (int i = 0; i < 32; i++) asm volatile("add.f32 %0, %1, 0f00000000;" : "=f"(p1[i]) : "f"(acc1[64 + i]));
#pragma unroll
            for (int i = 0; i < 16; i++) asm volatile("add.f32 %0, %1, 0f00000000;" : "=f"(p2[i]) : "f"(acc1[96 + i]));
        }
        wgmma_wait<0>();
        if (w4 == 3) {
            e_expect(bars + 8 * (B_XV + 2 + wg), X_BYTES);
            issue_xv(14, wg, bars + 8 * (B_XV + 2 + wg)); issue_xv(15, wg, bars + 8 * (B_XV + 2 + wg));
        }
        TSF(2);
#pragma unroll
        for (int h = 0; h < PK0; h++) store_half<0>(acc0, o, h);
#pragma unroll
        for (int h = PK0; h < 14; h++) pack_half(acc0, h, pk + (h - PK0) * 4);
#pragma unroll
        for (int h = PK0; h < (ASP > CSP ? ASP : CSP); h++) store_packed(o, h, pk + (h - PK0) * 4, ASP > CSP ? wg ^ 1 : wg);
        TSF(3);
    }
    uint32_t af[80];
    const uint32_t lm = sbase + wg * 16384 + (w4 * 16 + (lane & 15)) * 128 + (((lane >> 4) ^ (lane & 7)) << 4);
    auto ldfrag = [&](int st) {
#pragma unroll
        for (int kk = 0; kk < 4; kk++) {
            uint32_t* r = af + ((st - 11) * 4 + kk) * 4;
            asm volatile("ldmatrix.sync.aligned.m8n8.x4.shared.b16 {%0,%1,%2,%3}, [%4];" : "=r"(r[0]), "=r"(r[1]), "=r"(r[2]), "=r"(r[3])
                         : "r"((lm ^ (kk << 5)) + xofs(st, 0, 1)) : "memory");
        }
    };
    {
        ldfrag(11);
        asm volatile("bar.sync %0, 256;" ::"r"(2 + wg) : "memory");
        TSF(4);
        const uint32_t b16 = launder();
#pragma unroll
        for (int st = 11; st < 16; st++) {
            wgmma_fence();
#pragma unroll
            for (int kk = 0; kk < 4; kk++) {
                const int i = (st - 11) * 4 + kk;
                wgmma_rs_n128(p0, af + i * 4, dB(b16, wofs(st, kk)));
                if (kk == 0 && st < 15) {
                    if (st == 11) mbar_wait(bars + 8 * (B_XV + 2 + wg));
                    ldfrag(st + 1);
                }
                if (i % ISTEP == 0) {
                    const int h0 = ASP + i / ISTEP, h1 = CSP + i / ISTEP;
                    if (ASP == CSP) { if (h0 < 14) store_packed(o, h0, pk + (h0 - PK0) * 4, 1); }
                    else {
                        if (h0 < 14) store_packed(o, h0, pk + (h0 - PK0) * 4, wg ^ 1);
                        if (h1 < 14) store_packed(o, h1, pk + (h1 - PK0) * 4, wg);
                    }
                }
            }
        }
        wgmma_commit();
        asm volatile("bar.arrive %0, 256;" ::"r"(3 - wg) : "memory");
        TSF(5);
        wgmma_wait<0>();
        TSF(6);
#pragma unroll
        for (int h = 0; h < (BSP > DSP ? BSP : DSP); h++) if (h < BSP && h < DSP) store_half<64 * F_>(p0, o, h); else if (wg == (BSP > DSP ? 0 : 1)) store_half<64 * F_>(p0, o, h);
        TSF(7);
    }
    {
        asm volatile("bar.sync %0, 256;" ::"r"(2 + wg) : "memory");
        TSF(8);
        const uint32_t b16 = launder();
        wgmma_fence();
#pragma unroll
        for (int i = 0; i < 20; i++) {
            wgmma_rs_n64(p1, af + i * 4, dB(b16, wofs(11 + (i >> 2), i & 3) + 128 * 16));
            if (i % ISTEP2 == 0) {
                const int h0 = BSP + i / ISTEP2, h1 = DSP + i / ISTEP2;
                if (BSP == DSP) { if (h0 < 8) store_half<64 * F_>(p0, o, h0); }
                else {
                    if (h0 < 8) store_half<64 * F_>(p0, o, h0, wg ^ 1);
                    if (h1 < 8) store_half<64 * F_>(p0, o, h1, wg);
                }
            }
        }
        wgmma_commit();
#pragma unroll
        for (int i = 0; i < 20; i++) wgmma_rs_n32(p2, af + i * 4, dB(b16, wofs(11 + (i >> 2), i & 3) + 192 * 16));
        wgmma_commit();
        if (wg == 0) asm volatile("bar.arrive 3, 256;" ::: "memory");
        TSF(9);
        wgmma_wait<1>();
        store_tile<64 * F_ + 128, 0, 2>(p1, o);
        wgmma_wait<0>();
        TSK(4, 63); TSF(10);
        store_tile<64 * F_ + 192, 0, 1>(p2, o);
        TSK(4, 77); TSF(11);
    }
}

typedef CUresult (*EncodeTiledFn)(CUtensorMap*, CUtensorMapDataType, cuuint32_t, void*, const cuuint64_t*, const cuuint64_t*, const cuuint32_t*, const cuuint32_t*, CUtensorMapInterleave, CUtensorMapSwizzle, CUtensorMapL2promotion, CUtensorMapFloatOOBfill);

extern "C" void kernel_launch(void* const* d_in, const int* in_sizes, int n_in, void* d_out, int out_size) {
    static EncodeTiledFn enc = nullptr;
    static decltype(&fused_kernel<true>) kern = nullptr;
    static void *p_w = nullptr, *p_flags = nullptr, *p_prof = nullptr;
    if (!enc) {
        void* fn = nullptr; cudaDriverEntryPointQueryResult qr;
        cudaGetDriverEntryPoint("cuTensorMapEncodeTiled", &fn, cudaEnableDefault, &qr);
        enc = (EncodeTiledFn)fn;
        int dev = 0, rsv = 0;
        cudaGetDevice(&dev);
        cudaDeviceGetAttribute(&rsv, cudaDevAttrReservedSharedMemoryPerBlock, dev);
        kern = HARDBASE && rsv == 1024 ? fused_kernel<true> : fused_kernel<false>;
        cudaFuncSetAttribute(kern, cudaFuncAttributeMaxDynamicSharedMemorySize, SMEM_BYTES);
        cudaGetSymbolAddress(&p_w, g_w);
        cudaGetSymbolAddress(&p_flags, g_flags);
    }
    CUtensorMap tmx, tmx64, tmq;
    {
        cuuint64_t gdim[2] = {(cuuint64_t)F_, (cuuint64_t)D_};
        cuuint64_t gstr[1] = {(cuuint64_t)F_ * 4};
        cuuint32_t box[2] = {(cuuint32_t)BN, 16};
        cuuint32_t estr[2] = {1, 1};
        enc(&tmq, CU_TENSOR_MAP_DATA_TYPE_INT32, 2, d_in[1], gdim, gstr, box, estr, CU_TENSOR_MAP_INTERLEAVE_NONE,
            CU_TENSOR_MAP_SWIZZLE_NONE, CU_TENSOR_MAP_L2_PROMOTION_L2_128B, CU_TENSOR_MAP_FLOAT_OOB_FILL_NONE);
    }
    {
        cuuint64_t gdim[2] = {(cuuint64_t)D_, (cuuint64_t)S_};
        cuuint64_t gstr[1] = {(cuuint64_t)D_ * 2};
        cuuint32_t box[2] = {(cuuint32_t)BK, (cuuint32_t)BM};
        cuuint32_t estr[2] = {1, 1};
        enc(&tmx, CU_TENSOR_MAP_DATA_TYPE_BFLOAT16, 2, d_in[0], gdim, gstr, box, estr, CU_TENSOR_MAP_INTERLEAVE_NONE,
            CU_TENSOR_MAP_SWIZZLE_128B, XPROMO, CU_TENSOR_MAP_FLOAT_OOB_FILL_NONE);
        box[1] = 64;
        enc(&tmx64, CU_TENSOR_MAP_DATA_TYPE_BFLOAT16, 2, d_in[0], gdim, gstr, box, estr, CU_TENSOR_MAP_INTERLEAVE_NONE,
            CU_TENSOR_MAP_SWIZZLE_128B, XPROMO, CU_TENSOR_MAP_FLOAT_OOB_FILL_NONE);
    }
    kern<<<128, 256, SMEM_BYTES>>>((const int*)d_in[1], (const unsigned short*)d_in[2], (__nv_bfloat16*)d_out, (uint4*)p_w, (unsigned*)p_flags, 0x80000000u, tmq, tmx64, tmx
    );
    (void)p_prof;
}
```

```cpp
#include <cuda_runtime.h>
#include <cuda_bf16.h>
#include <cuda.h>
#include <stdint.h>
#include <stdio.h>

#define LA 2
#define XPROMO CU_TENSOR_MAP_L2_PROMOTION_L2_128B
#define CSPLIT 5
#define FADDPOS 1
#define BSPLIT 4
#define DSPLIT 4
#define FLAGPOS 1
#define RAW1POS 5
#define PIPE 6
#define PR1 1100
#define LK 1
#define PX0 1000
#define PX1 100000
#define R2AT 0
#define R3AT 3
#define R4AT 4
#define W1EARLY 1
#define PR2 1700
#define PSTEP 0
#define PSBASE 0
#define NOW 2
#define R34AT 0
#define R1MODE 1
#define ST2 1
#define PR34 3500
#define DEADT 300
#define PPOLL 2800
#define ALLONLY 0
#define X1POST 0
#define W3FIRST 1
#define W1BY 3
#define W1D 150
#define F2POS 1
#define W2POS 0
#define W2D 200
#define W3D 0
#define W4L2 0
#define R3W1 4
#define VGRAN 32
#define X2POS 0
#define VSPLIT 0
#define NF 4
#define PAIR 0
#define ZPOS 10
#define PFX 0
#define PFXB 2
#define ASP 10
#define CSP 10
#define BSP 8
#define DSP 6
#define ISTEP 2
#define ISTEP2 2
#define PEEL 1
#define ILV 0
#define R4W0 0
#define PLAG 0
#define PSTA 110
#define PSF 2
#define PSTB 110
#define PSB0 200
#define L11 2
#define L12 6
#define L13 0
#define HARDBASE 1

constexpr int S_ = 2048, D_ = 1024, F_ = 3584;
constexpr int BM = 256, BN = 224, BK = 64;
constexpr int X_BYTES = BM * BK * 2;
constexpr int W_BYTES = BN * BK * 2;
constexpr int CHUNK_BYTES = BN * 16;
constexpr int OFF_X = 0;
constexpr int OFF_W = 3 * X_BYTES;
constexpr int OFF_STG = OFF_W + 3 * W_BYTES;
constexpr int OFF_LUT = OFF_W + 4 * W_BYTES;
constexpr int OFF_BAR = OFF_LUT + 7 * 2048;
constexpr int OFF_PROF = OFF_BAR + 1024;
constexpr int SMEM_BYTES = OFF_PROF + 1024 + 1024;
constexpr int B_FULL = 0;
constexpr int B_XV = 12;
constexpr int B_WF = 17;
constexpr int B_EMPTY = 22;
constexpr int B_DQ = 34;
constexpr int B_SLAB = 42;
constexpr int B_L = 34;
constexpr int B_X15 = 35;
constexpr int B_LUT = 46;

__device__ __align__(1024) uint4 g_w[(size_t)F_ * D_ / 8];
__device__ __align__(128) unsigned g_flags[16 * 32];

__device__ __forceinline__ uint32_t smem_u32(const void* p) { return (uint32_t)__cvta_generic_to_shared(p); }
__device__ __forceinline__ void mbar_init(uint32_t bar, uint32_t cnt) { asm volatile("mbarrier.init.shared::cta.b64 [%0], %1;" ::"r"(bar), "r"(cnt) : "memory"); }
__device__ __forceinline__ void mbar_wait(uint32_t bar) {
    asm volatile("{\n.reg .pred p;\nWAIT_LOOP:\nmbarrier.try_wait.parity.shared::cta.b64 p, [%0], 0;\n@p bra WAIT_DONE;\nbra WAIT_LOOP;\nWAIT_DONE:\n}" ::"r"(bar) : "memory");
}
__device__ __forceinline__ void e_arrive(uint32_t bar) {
    asm volatile("{\n.reg .pred p;\nelect.sync _|p, 0xffffffff;\n@p mbarrier.arrive.shared::cta.b64 _, [%0];\n}" ::"r"(bar) : "memory");
}
__device__ __forceinline__ void e_expect(uint32_t bar, uint32_t bytes) {
    asm volatile("{\n.reg .pred p;\nelect.sync _|p, 0xffffffff;\n@p mbarrier.arrive.expect_tx.shared::cta.b64 _, [%0], %1;\n}" ::"r"(bar), "r"(bytes) : "memory");
}
__device__ __forceinline__ void e_tma(uint32_t bar, const CUtensorMap* tm, uint32_t d0, int x0, int y0) {
    asm volatile("{\n.reg .pred p;\nelect.sync _|p, 0xffffffff;\n"
                 "@p cp.async.bulk.tensor.2d.shared::cluster.global.mbarrier::complete_tx::bytes [%2], [%1, {%3, %4}], [%0];\n}"
                 ::"r"(bar), "l"(tm), "r"(d0), "r"(x0), "r"(y0) : "memory");
}
__device__ __forceinline__ void e_bulk(uint32_t bar, uint32_t bytes, uint32_t dst, const void* src) {
    asm volatile("{\n.reg .pred p;\nelect.sync _|p, 0xffffffff;\n"
                 "@p mbarrier.arrive.expect_tx.shared::cta.b64 _, [%0], %1;\n"
                 "@p cp.async.bulk.shared::cluster.global.mbarrier::complete_tx::bytes [%2], [%3], %1, [%0];\n}"
                 ::"r"(bar), "r"(bytes), "r"(dst), "l"(src) : "memory");
}
__device__ __forceinline__ void e_bulk_p(uint32_t on, uint32_t bar, uint32_t bytes, uint32_t dst, const void* src) {
    if (on) asm volatile("{\n.reg .pred p;\nelect.sync _|p, 0xffffffff;\n"
                         "@p cp.async.bulk.shared::cluster.global.mbarrier::complete_tx::bytes [%2], [%3], %1, [%0];\n}"
                         ::"r"(bar), "r"(bytes), "r"(dst), "l"(src) : "memory");
}
__device__ __forceinline__ void e_prefetch2d(const CUtensorMap* tm, int x, int y) {
    asm volatile("{\n.reg .pred p;\nelect.sync _|p, 0xffffffff;\n@p cp.async.bulk.prefetch.tensor.2d.L2.global [%0, {%1, %2}];\n}" ::"l"(tm), "r"(x), "r"(y) : "memory");
}
#define FASTREL 0
__device__ __forceinline__ void e_publish(unsigned* flag) {
    asm volatile("{\n.reg .pred p;\nelect.sync _|p, 0xffffffff;\n@p red.release.gpu.global.add.u32 [%0], 1;\n}" ::"l"(flag) : "memory");
}
__device__ __forceinline__ void e_red(unsigned* flag, unsigned v) {
    asm volatile("{\n.reg .pred p;\nelect.sync _|p, 0xffffffff;\n@p red.relaxed.gpu.global.add.u32 [%0], %1;\n}" ::"l"(flag), "r"(v) : "memory");
}
__device__ __forceinline__ bool mbar_test(uint32_t bar) {
    uint32_t r;
    asm volatile("{\n.reg .pred p;\nmbarrier.test_wait.parity.shared::cta.b64 p, [%1], 0;\nselp.u32 %0, 1, 0, p;\n}" : "=r"(r) : "r"(bar) : "memory");
    return __all_sync(0xffffffff, r != 0);
}
template <int V> struct IC { static constexpr int value = V; };
__device__ __forceinline__ unsigned ld_flag(const unsigned* f) { unsigned v; asm volatile("ld.relaxed.gpu.global.u32 %0, [%1];" : "=r"(v) : "l"(f) : "memory"); return v; }
__device__ __forceinline__ void finish_poll(const unsigned* f, unsigned v, unsigned target) {
    int n = 0;
    while (!__all_sync(0xffffffff, (int)(v - target) >= 0) && ++n < 4000000) v = ld_flag(f);
    asm volatile("fence.acquire.gpu;" ::: "memory");
    asm volatile("fence.proxy.async.global;" ::: "memory");
}
template <typename T> __device__ __forceinline__ T* ptr_add(T* base, uint32_t off) {
    uint64_t r;
    asm("{\n.reg .u32 l, h;\nmov.b64 {l, h}, %1;\nadd.cc.u32 l, l, %2;\naddc.u32 h, h, 0;\nmov.b64 %0, {l, h};\n}" : "=l"(r) : "l"(base), "r"(off));
    return (T*)r;
}
__device__ __forceinline__ void wgmma_fence() { asm volatile("wgmma.fence.sync.aligned;" ::: "memory"); }
__device__ __forceinline__ void wgmma_commit() { asm volatile("wgmma.commit_group.sync.aligned;" ::: "memory"); }
template <int N> __device__ __forceinline__ void wgmma_wait() { asm volatile("wgmma.wait_group.sync.aligned %0;" ::"n"(N) : "memory"); }
__device__ __forceinline__ void wgmma_m64n224k16(float (&d)[112], uint64_t da, uint64_t db, int scale_d) {
    asm volatile(
        "{\n.reg .pred p;\nsetp.ne.b32 p, %114, 0;\n"
        "wgmma.mma_async.sync.aligned.m64n224k16.f32.bf16.bf16 "
        "{%0, %1, %2, %3, %4, %5, %6, %7, %8, %9, %10, %11, %12, %13, %14, %15, "
        "%16, %17, %18, %19, %20, %21, %22, %23, %24, %25, %26, %27, %28, %29, %30, %31, "
        "%32, %33, %34, %35, %36, %37, %38, %39, %40, %41, %42, %43, %44, %45, %46, %47, "
        "%48, %49, %50, %51, %52, %53, %54, %55, %56, %57, %58, %59, %60, %61, %62, %63, "
        "%64, %65, %66, %67, %68, %69, %70, %71, %72, %73, %74, %75, %76, %77, %78, %79, "
        "%80, %81, %82, %83, %84, %85, %86, %87, %88, %89, %90, %91, %92, %93, %94, %95, "
        "%96, %97, %98, %99, %100, %101, %102, %103, %104, %105, %106, %107, %108, %109, %110, %111}, "
        "%112, %113, p, 1, 1, 0, 0;\n}\n"
        : "+f"(d[0]), "+f"(d[1]), "+f"(d[2]), "+f"(d[3]), "+f"(d[4]), "+f"(d[5]), "+f"(d[6]), "+f"(d[7]),
          "+f"(d[8]), "+f"(d[9]), "+f"(d[10]), "+f"(d[11]), "+f"(d[12]), "+f"(d[13]), "+f"(d[14]), "+f"(d[15]),
          "+f"(d[16]), "+f"(d[17]), "+f"(d[18]), "+f"(d[19]), "+f"(d[20]), "+f"(d[21]), "+f"(d[22]), "+f"(d[23]),
          "+f"(d[24]), "+f"(d[25]), "+f"(d[26]), "+f"(d[27]), "+f"(d[28]), "+f"(d[29]), "+f"(d[30]), "+f"(d[31]),
          "+f"(d[32]), "+f"(d[33]), "+f"(d[34]), "+f"(d[35]), "+f"(d[36]), "+f"(d[37]), "+f"(d[38]), "+f"(d[39]),
          "+f"(d[40]), "+f"(d[41]), "+f"(d[42]), "+f"(d[43]), "+f"(d[44]), "+f"(d[45]), "+f"(d[46]), "+f"(d[47]),
          "+f"(d[48]), "+f"(d[49]), "+f"(d[50]), "+f"(d[51]), "+f"(d[52]), "+f"(d[53]), "+f"(d[54]), "+f"(d[55]),
          "+f"(d[56]), "+f"(d[57]), "+f"(d[58]), "+f"(d[59]), "+f"(d[60]), "+f"(d[61]), "+f"(d[62]), "+f"(d[63]),
          "+f"(d[64]), "+f"(d[65]), "+f"(d[66]), "+f"(d[67]), "+f"(d[68]), "+f"(d[69]), "+f"(d[70]), "+f"(d[71]),
          "+f"(d[72]), "+f"(d[73]), "+f"(d[74]), "+f"(d[75]), "+f"(d[76]), "+f"(d[77]), "+f"(d[78]), "+f"(d[79]),
          "+f"(d[80]), "+f"(d[81]), "+f"(d[82]), "+f"(d[83]), "+f"(d[84]), "+f"(d[85]), "+f"(d[86]), "+f"(d[87]),
          "+f"(d[88]), "+f"(d[89]), "+f"(d[90]), "+f"(d[91]), "+f"(d[92]), "+f"(d[93]), "+f"(d[94]), "+f"(d[95]),
          "+f"(d[96]), "+f"(d[97]), "+f"(d[98]), "+f"(d[99]), "+f"(d[100]), "+f"(d[101]), "+f"(d[102]), "+f"(d[103]),
          "+f"(d[104]), "+f"(d[105]), "+f"(d[106]), "+f"(d[107]), "+f"(d[108]), "+f"(d[109]), "+f"(d[110]), "+f"(d[111])
        : "l"(da), "l"(db), "r"(scale_d));
}

__device__ __forceinline__ void wgmma_rs_n32(float (&d)[16], const uint32_t* a, uint64_t db) {
    asm volatile("wgmma.mma_async.sync.aligned.m64n32k16.f32.bf16.bf16 {%0, %1, %2, %3, %4, %5, %6, %7, %8, %9, %10, %11, %12, %13, %14, %15}, {%16, %17, %18, %19}, %20, 1, 1, 1, 0;"
        : "+f"(d[0]), "+f"(d[1]), "+f"(d[2]), "+f"(d[3]), "+f"(d[4]), "+f"(d[5]), "+f"(d[6]), "+f"(d[7]), "+f"(d[8]), "+f"(d[9]), "+f"(d[10]), "+f"(d[11]), "+f"(d[12]), "+f"(d[13]), "+f"(d[14]), "+f"(d[15])
        : "r"(a[0]), "r"(a[1]), "r"(a[2]), "r"(a[3]), "l"(db));
}
__device__ __forceinline__ void wgmma_ss_n32(float (&d)[16], uint64_t da, uint64_t db) {
    asm volatile("wgmma.mma_async.sync.aligned.m64n32k16.f32.bf16.bf16 {%0, %1, %2, %3, %4, %5, %6, %7, %8, %9, %10, %11, %12, %13, %14, %15}, %16, %17, 1, 1, 1, 0, 0;"
        : "+f"(d[0]), "+f"(d[1]), "+f"(d[2]), "+f"(d[3]), "+f"(d[4]), "+f"(d[5]), "+f"(d[6]), "+f"(d[7]), "+f"(d[8]), "+f"(d[9]), "+f"(d[10]), "+f"(d[11]), "+f"(d[12]), "+f"(d[13]), "+f"(d[14]), "+f"(d[15])
        : "l"(da), "l"(db));
}
__device__ __forceinline__ void wgmma_rs_n64(float (&d)[32], const uint32_t* a, uint64_t db) {
    asm volatile("wgmma.mma_async.sync.aligned.m64n64k16.f32.bf16.bf16 {%0, %1, %2, %3, %4, %5, %6, %7, %8, %9, %10, %11, %12, %13, %14, %15, %16, %17, %18, %19, %20, %21, %22, %23, %24, %25, %26, %27, %28, %29, %30, %31}, {%32, %33, %34, %35}, %36, 1, 1, 1, 0;"
        : "+f"(d[0]), "+f"(d[1]), "+f"(d[2]), "+f"(d[3]), "+f"(d[4]), "+f"(d[5]), "+f"(d[6]), "+f"(d[7]), "+f"(d[8]), "+f"(d[9]), "+f"(d[10]), "+f"(d[11]), "+f"(d[12]), "+f"(d[13]), "+f"(d[14]), "+f"(d[15]), "+f"(d[16]), "+f"(d[17]), "+f"(d[18]), "+f"(d[19]), "+f"(d[20]), "+f"(d[21]), "+f"(d[22]), "+f"(d[23]), "+f"(d[24]), "+f"(d[25]), "+f"(d[26]), "+f"(d[27]), "+f"(d[28]), "+f"(d[29]), "+f"(d[30]), "+f"(d[31])
        : "r"(a[0]), "r"(a[1]), "r"(a[2]), "r"(a[3]), "l"(db));
}
__device__ __forceinline__ void wgmma_ss_n64(float (&d)[32], uint64_t da, uint64_t db) {
    asm volatile("wgmma.mma_async.sync.aligned.m64n64k16.f32.bf16.bf16 {%0, %1, %2, %3, %4, %5, %6, %7, %8, %9, %10, %11, %12, %13, %14, %15, %16, %17, %18, %19, %20, %21, %22, %23, %24, %25, %26, %27, %28, %29, %30, %31}, %32, %33, 1, 1, 1, 0, 0;"
        : "+f"(d[0]), "+f"(d[1]), "+f"(d[2]), "+f"(d[3]), "+f"(d[4]), "+f"(d[5]), "+f"(d[6]), "+f"(d[7]), "+f"(d[8]), "+f"(d[9]), "+f"(d[10]), "+f"(d[11]), "+f"(d[12]), "+f"(d[13]), "+f"(d[14]), "+f"(d[15]), "+f"(d[16]), "+f"(d[17]), "+f"(d[18]), "+f"(d[19]), "+f"(d[20]), "+f"(d[21]), "+f"(d[22]), "+f"(d[23]), "+f"(d[24]), "+f"(d[25]), "+f"(d[26]), "+f"(d[27]), "+f"(d[28]), "+f"(d[29]), "+f"(d[30]), "+f"(d[31])
        : "l"(da), "l"(db));
}
__device__ __forceinline__ void wgmma_rs_n128(float (&d)[64], const uint32_t* a, uint64_t db) {
    asm volatile("wgmma.mma_async.sync.aligned.m64n128k16.f32.bf16.bf16 {%0, %1, %2, %3, %4, %5, %6, %7, %8, %9, %10, %11, %12, %13, %14, %15, %16, %17, %18, %19, %20, %21, %22, %23, %24, %25, %26, %27, %28, %29, %30, %31, %32, %33, %34, %35, %36, %37, %38, %39, %40, %41, %42, %43, %44, %45, %46, %47, %48, %49, %50, %51, %52, %53, %54, %55, %56, %57, %58, %59, %60, %61, %62, %63}, {%64, %65, %66, %67}, %68, 1, 1, 1, 0;"
        : "+f"(d[0]), "+f"(d[1]), "+f"(d[2]), "+f"(d[3]), "+f"(d[4]), "+f"(d[5]), "+f"(d[6]), "+f"(d[7]), "+f"(d[8]), "+f"(d[9]), "+f"(d[10]), "+f"(d[11]), "+f"(d[12]), "+f"(d[13]), "+f"(d[14]), "+f"(d[15]), "+f"(d[16]), "+f"(d[17]), "+f"(d[18]), "+f"(d[19]), "+f"(d[20]), "+f"(d[21]), "+f"(d[22]), "+f"(d[23]), "+f"(d[24]), "+f"(d[25]), "+f"(d[26]), "+f"(d[27]), "+f"(d[28]), "+f"(d[29]), "+f"(d[30]), "+f"(d[31]), "+f"(d[32]), "+f"(d[33]), "+f"(d[34]), "+f"(d[35]), "+f"(d[36]), "+f"(d[37]), "+f"(d[38]), "+f"(d[39]), "+f"(d[40]), "+f"(d[41]), "+f"(d[42]), "+f"(d[43]), "+f"(d[44]), "+f"(d[45]), "+f"(d[46]), "+f"(d[47]), "+f"(d[48]), "+f"(d[49]), "+f"(d[50]), "+f"(d[51]), "+f"(d[52]), "+f"(d[53]), "+f"(d[54]), "+f"(d[55]), "+f"(d[56]), "+f"(d[57]), "+f"(d[58]), "+f"(d[59]), "+f"(d[60]), "+f"(d[61]), "+f"(d[62]), "+f"(d[63])
        : "r"(a[0]), "r"(a[1]), "r"(a[2]), "r"(a[3]), "l"(db));
}
__device__ __forceinline__ void wgmma_ss_n128(float (&d)[64], uint64_t da, uint64_t db) {
    asm volatile("wgmma.mma_async.sync.aligned.m64n128k16.f32.bf16.bf16 {%0, %1, %2, %3, %4, %5, %6, %7, %8, %9, %10, %11, %12, %13, %14, %15, %16, %17, %18, %19, %20, %21, %22, %23, %24, %25, %26, %27, %28, %29, %30, %31, %32, %33, %34, %35, %36, %37, %38, %39, %40, %41, %42, %43, %44, %45, %46, %47, %48, %49, %50, %51, %52, %53, %54, %55, %56, %57, %58, %59, %60, %61, %62, %63}, %64, %65, 1, 1, 1, 0, 0;"
        : "+f"(d[0]), "+f"(d[1]), "+f"(d[2]), "+f"(d[3]), "+f"(d[4]), "+f"(d[5]), "+f"(d[6]), "+f"(d[7]), "+f"(d[8]), "+f"(d[9]), "+f"(d[10]), "+f"(d[11]), "+f"(d[12]), "+f"(d[13]), "+f"(d[14]), "+f"(d[15]), "+f"(d[16]), "+f"(d[17]), "+f"(d[18]), "+f"(d[19]), "+f"(d[20]), "+f"(d[21]), "+f"(d[22]), "+f"(d[23]), "+f"(d[24]), "+f"(d[25]), "+f"(d[26]), "+f"(d[27]), "+f"(d[28]), "+f"(d[29]), "+f"(d[30]), "+f"(d[31]), "+f"(d[32]), "+f"(d[33]), "+f"(d[34]), "+f"(d[35]), "+f"(d[36]), "+f"(d[37]), "+f"(d[38]), "+f"(d[39]), "+f"(d[40]), "+f"(d[41]), "+f"(d[42]), "+f"(d[43]), "+f"(d[44]), "+f"(d[45]), "+f"(d[46]), "+f"(d[47]), "+f"(d[48]), "+f"(d[49]), "+f"(d[50]), "+f"(d[51]), "+f"(d[52]), "+f"(d[53]), "+f"(d[54]), "+f"(d[55]), "+f"(d[56]), "+f"(d[57]), "+f"(d[58]), "+f"(d[59]), "+f"(d[60]), "+f"(d[61]), "+f"(d[62]), "+f"(d[63])
        : "l"(da), "l"(db));
}

__device__ __forceinline__ uint32_t pack_bf16(float lo, float hi) {
    uint32_t r; asm("cvt.rn.bf16x2.f32 %0, %1, %2;" : "=r"(r) : "f"(hi), "f"(lo)); return r;
}
__device__ __forceinline__ uint32_t lds32(uint32_t a) { uint32_t v; asm volatile("ld.shared.b32 %0, [%1];" : "=r"(v) : "r"(a)); return v; }
__device__ __forceinline__ void sts32(uint32_t a, uint32_t v) { asm volatile("st.shared.b32 [%0], %1;" ::"r"(a), "r"(v) : "memory"); }
__device__ __forceinline__ void sts128(uint32_t a, uint4 v) { asm volatile("st.shared.v4.b32 [%0], {%1,%2,%3,%4};" ::"r"(a), "r"(v.x), "r"(v.y), "r"(v.z), "r"(v.w) : "memory"); }
__device__ __forceinline__ void stg128(void* p, uint4 v) { asm volatile("st.global.v4.b32 [%0], {%1,%2,%3,%4};" ::"l"(p), "r"(v.x), "r"(v.y), "r"(v.z), "r"(v.w) : "memory"); }
__device__ __forceinline__ void cp16(uint32_t dst, const void* src) { asm volatile("cp.async.cg.shared.global [%0], [%1], 16;" ::"r"(dst), "l"(src) : "memory"); }
__device__ __forceinline__ void cp_commit() { asm volatile("cp.async.commit_group;" ::: "memory"); }
template <int N> __device__ __forceinline__ void cp_wait() { asm volatile("cp.async.wait_group %0;" ::"n"(N) : "memory"); }
__device__ __forceinline__ uint4 dequant8(uint32_t raw, uint32_t lut_a) {
    uint32_t v[8];
#pragma unroll
    for (int i = 0; i < 8; i++) v[i] = lds32(raw + i * 128);
#pragma unroll
    for (int i = 0; i < 8; i++) v[i] = lds32(lut_a + v[i] * 128);
    uint4 o;
    o.x = __byte_perm(v[0], v[1], 0x5410); o.y = __byte_perm(v[2], v[3], 0x5410);
    o.z = __byte_perm(v[4], v[5], 0x5410); o.w = __byte_perm(v[6], v[7], 0x5410);
    return o;
}
__device__ __forceinline__ uint32_t prmt(uint32_t a, uint32_t b, uint32_t c) { uint32_t r; asm("prmt.b32 %0, %1, %2, %3;" : "=r"(r) : "r"(a), "r"(b), "r"(c)); return r; }
__device__ __forceinline__ uint4 lookup8_reg(const uint32_t* c, const uint32_t (&T)[8], uint32_t two31) {
    uint32_t o[4];
#pragma unroll
    for (int h = 0; h < 2; h++) {
        const uint32_t sel = c[4 * h] + c[4 * h + 1] * 16 + c[4 * h + 2] * 256 + c[4 * h + 3] * 4096;
        const uint32_t s7 = sel & 0x7777u;
        uint32_t m;
        asm("lop3.b32 %0, %1, %2, 0x3210, 0xEA;" : "=r"(m) : "r"(__umulhi(sel, two31)), "r"(0x4444u));
        const uint32_t lo = prmt(prmt(T[0], T[1], s7), prmt(T[2], T[3], s7), m);
        const uint32_t hi = prmt(prmt(T[4], T[5], s7), prmt(T[6], T[7], s7), m);
        o[2 * h] = prmt(lo, hi, 0x5140u); o[2 * h + 1] = prmt(lo, hi, 0x7362u);
    }
    return make_uint4(o[0], o[1], o[2], o[3]);
}
template <int OFF, int G0, int G1, int N>
__device__ __forceinline__ void store_tile(const float (&acc)[N], __nv_bfloat16* o) {
#pragma unroll
    for (int G = G0; G < G1; G++) {
        uint4 v;
        v.x = pack_bf16(acc[G * 16 + 0], acc[G * 16 + 1]); v.y = pack_bf16(acc[G * 16 + 4], acc[G * 16 + 5]);
        v.z = pack_bf16(acc[G * 16 + 8], acc[G * 16 + 9]); v.w = pack_bf16(acc[G * 16 + 12], acc[G * 16 + 13]);
        stg128(o + OFF + G * 32, v);
        v.x = pack_bf16(acc[G * 16 + 2], acc[G * 16 + 3]); v.y = pack_bf16(acc[G * 16 + 6], acc[G * 16 + 7]);
        v.z = pack_bf16(acc[G * 16 + 10], acc[G * 16 + 11]); v.w = pack_bf16(acc[G * 16 + 14], acc[G * 16 + 15]);
        stg128(o + OFF + 8 * F_ + G * 32, v);
    }
}
template <int OFF, int N>
__device__ __forceinline__ void store_half(const float (&acc)[N], __nv_bfloat16* o, int H, int on = 1) {
    const int b = (H >> 1) * 16 + (H & 1) * 2;
    uint4 v;
    v.x = pack_bf16(acc[b + 0], acc[b + 1]); v.y = pack_bf16(acc[b + 4], acc[b + 5]);
    v.z = pack_bf16(acc[b + 8], acc[b + 9]); v.w = pack_bf16(acc[b + 12], acc[b + 13]);
    asm volatile("{\n.reg .pred p;\nsetp.ne.b32 p, %5, 0;\n@p st.global.v4.b32 [%0], {%1,%2,%3,%4};\n}"
                 ::"l"(o + OFF + (H & 1) * 8 * F_ + (H >> 1) * 32), "r"(v.x), "r"(v.y), "r"(v.z), "r"(v.w), "r"(on) : "memory");
}
template <int N>
__device__ __forceinline__ void pack_half(const float (&acc)[N], int H, uint32_t* r) {
    const int b = (H >> 1) * 16 + (H & 1) * 2;
#pragma unroll
    for (int i = 0; i < 4; i++) asm volatile("cvt.rn.bf16x2.f32 %0, %1, %2;" : "=r"(r[i]) : "f"(acc[b + 4 * i + 1]), "f"(acc[b + 4 * i]));
}
__device__ __forceinline__ void store_packed(__nv_bfloat16* o, int H, const uint32_t* r, int on) {
    asm volatile("{\n.reg .pred p;\nsetp.ne.b32 p, %5, 0;\n@p st.global.v4.b32 [%0], {%1,%2,%3,%4};\n}"
                 ::"l"(o + (H & 1) * 8 * F_ + (H >> 1) * 32), "r"(r[0]), "r"(r[1]), "r"(r[2]), "r"(r[3]), "r"(on) : "memory");
}
constexpr int NROUNDS = 8;
constexpr unsigned long long R_FIRST = 0xFDB97543ull, R_BATCH = 0x60050400ull, R_DOUBLE = 0x7C;
constexpr unsigned long long W_FLAG = 0x600504000ull;
constexpr unsigned L1_MASK = W4L2 ? 0x2A : 0x2E, L2_MASK = W4L2 ? 0x1EA : 0x1E8; constexpr int W12_AT = 8;
constexpr int NFAST = NF;
__device__ __forceinline__ int round_first(int r) { return (int)(R_FIRST >> (4 * r)) & 15; }
__device__ __forceinline__ int round_batch(int r) { return (int)(R_BATCH >> (4 * r)) & 15; }

#define TSK(w, i)
#define TSF(i)
#define TSP(i)
#define TSQ(i)
#define PW 0
#define TS9(i)
#define TS8(i)
#define TSW(w, i)

template <bool HARD>
__global__ void __launch_bounds__(256, 1)
fused_kernel(const int* __restrict__ qw, const unsigned short* __restrict__ lut, __nv_bfloat16* __restrict__ out,
             uint4* __restrict__ wscr, unsigned* __restrict__ flags, const uint32_t two31,
             const __grid_constant__ CUtensorMap tmq, const __grid_constant__ CUtensorMap tmx64, const __grid_constant__ CUtensorMap tmx
) {
    extern __shared__ uint8_t smem_raw[];
    const uint32_t sbase = HARD ? 1024u : (smem_u32(smem_raw) + 1023) & ~1023u;
    const uint32_t bars = sbase + OFF_BAR;
    const int tid = threadIdx.x, lane = tid & 31;
    const int mt = blockIdx.x & 7, g = blockIdx.x >> 3;
    unsigned clk0; asm volatile("mov.u32 %0, %%clock;" : "=r"(clk0));
    constexpr int SLAB_BYTES = 16 * BN * 4, OFF_SLAB0 = OFF_W + 2 * W_BYTES, OFF_SLAB2 = OFF_X + 2 * X_BYTES;
    const int warp = __shfl_sync(0xffffffff, tid >> 5, 0);
    if (tid >= 224) {
        asm volatile("{\n.reg .pred p;\nelect.sync _|p, 0xffffffff;\n"
                     "@p mbarrier.init.shared::cta.b64 [%0], 1;\n"
                     "@p fence.mbarrier_init.release.cluster;\n"
                     "@p mbarrier.arrive.expect_tx.shared::cta.b64 _, [%0], %1;\n"
                     "@p cp.async.bulk.tensor.2d.shared::cluster.global.mbarrier::complete_tx::bytes [%3], [%2, {%4, 0}], [%0];\n}"
                     ::"r"(bars + 8 * B_SLAB), "n"(SLAB_BYTES), "l"(&tmq), "r"(sbase + OFF_SLAB0), "r"(g * BN) : "memory");
    } else {
        const unsigned short* lp = ptr_add(lut, ((lane >> 2) * F_ + g * BN + (tid & ~31) + (lane & 3) * 8) * 2);
        asm volatile("cp.async.cg.shared.global [%0], [%1], 16;\ncp.async.cg.shared.global [%0+512], [%1+57344], 16;\ncp.async.commit_group;"
                     ::"r"(sbase + OFF_STG + (tid >> 5) * 4096 + lane * 16), "l"(lp) : "memory");
    }
    const int sl = warp - 3;
    auto load_slab = [&]() {
        e_tma(bars + 8 * (B_SLAB + sl), &tmq, sbase + (sl < 2 ? OFF_SLAB0 : OFF_SLAB2 - 2 * SLAB_BYTES) + sl * SLAB_BYTES, g * BN, sl * 16);
    };
    if (warp >= 4 && warp < 7) {
        asm volatile("{\n.reg .pred p;\nelect.sync _|p, 0xffffffff;\n"
                     "@p mbarrier.init.shared::cta.b64 [%0], 1;\n"
                     "@p fence.mbarrier_init.release.cluster;\n"
                     "@p mbarrier.arrive.expect_tx.shared::cta.b64 _, [%0], %1;\n}"
                     ::"r"(bars + 8 * (B_SLAB + sl)), "n"(SLAB_BYTES) : "memory");
        if (sl < NOW) load_slab();
    } else if (warp < 2) {
        asm volatile("{\n.reg .pred p;\nelect.sync _|p, 0xffffffff;\n"
                     "@p mbarrier.init.shared::cta.b64 [%0], %1;\n"
                     "@p fence.mbarrier_init.release.cluster;\n}" ::"r"(bars + 8 * (warp ? B_LUT : B_FULL)), "r"(8 - warp) : "memory");
    }
    asm volatile("bar.sync 1, 256;" ::: "memory");
    TSQ(0);
    const int wg = warp >> 2;

    const int fl = 8 * ((lane & 7) >> 1) + 2 * (lane >> 3) + (lane & 1);
    const uint32_t lut_a = sbase + OFF_LUT + warp * 2048 + lane * 4;
    const uint32_t stg = sbase + OFF_STG + warp * 4096;
    unsigned* myflags = flags + g * 32;
    const uint4* wgrp = wscr + (size_t)g * 128 * BN;
    unsigned target = 0;

    auto issue_x = [&](int s, int slot) {
        e_tma(bars + 8 * (B_FULL + s), &tmx, sbase + OFF_X + slot * X_BYTES, s * BK, mt * BM);
    };
    auto pf_x = [&](int s, int row0) { e_prefetch2d(&tmx64, s * BK, row0); };
    auto issue_xv = [&](int v, int w, uint32_t bar) {
        const uint32_t dst = sbase + OFF_X + (v & 1) * X_BYTES + w * 16384;
        const int k0 = (12 + 2 * (v & 1)) * BK, r0 = mt * BM + w * 128 + ((v >> 1) & 1) * 64;
        e_tma(bar, &tmx64, dst, k0, r0);
        e_tma(bar, &tmx64, dst + 8192, k0 + BK, r0);
    };
    auto issue_w = [&](int s, int slot, int bar) {
        e_bulk(bars + 8 * bar, W_BYTES, sbase + OFF_W + slot * W_BYTES, wgrp + s * 8 * BN);
    };
    auto load_raw = [&](int t) {
        if (t < 16) {
            const int* src = ptr_add(qw, (uint32_t)(((t * BK + mt * 8 + (lane >> 3)) * F_ + g * BN + warp * 32 + (lane & 7) * 4) * 4));
            asm volatile("cp.async.cg.shared.global [%0], [%1], 16;\ncp.async.cg.shared.global [%0+512], [%1+57344], 16;"
                         ::"r"(stg + (t & 3) * 1024 + lane * 16), "l"(src) : "memory");
        }
        cp_commit();
    };
    auto load_blk = [&](int t, int c) {
        const int* src = ptr_add(qw, (uint32_t)(((t * BK + mt * 8 + (lane >> 3)) * F_ + g * BN + c * 32 + (lane & 7) * 4) * 4));
        asm volatile("cp.async.cg.shared.global [%0], [%1], 16;\ncp.async.cg.shared.global [%0+512], [%1+57344], 16;"
                     ::"r"(sbase + OFF_STG + c * 4096 + t * 1024 + lane * 16), "l"(src) : "memory");
    };
    auto foreign = [&](int t) {
        const int c = warp ^ 4;
        stg128(ptr_add(wscr, (uint32_t)(((g * 128 + t * 8 + mt) * BN + c * 32 + lane) * 16)),
               dequant8(sbase + OFF_STG + c * 4096 + t * 1024 + fl * 4, sbase + OFF_LUT + c * 2048 + lane * 4));
        TSW(4, 5);
    };
    auto my_unit = [&](int t) { return ptr_add(wscr, (uint32_t)(((g * 128 + t * 8 + mt) * BN + warp * 32 + lane) * 16)); };
    auto coop = [&](int t) {
        cp_wait<LA - 1>();
        __syncwarp();
        load_raw(t + LA);
        stg128(my_unit(t), dequant8(stg + (t & 3) * 1024 + fl * 4, lut_a));

    };
    auto coop2 = [&](int t) {
        cp_wait<0>();
        __syncwarp();
        if (t < 14) {
            const int* src = ptr_add(qw, (uint32_t)((((t + 2) * BK + mt * 8 + (lane >> 3)) * F_ + g * BN + warp * 32 + (lane & 7) * 4) * 4));
            asm volatile("cp.async.cg.shared.global [%0], [%1], 16;\ncp.async.cg.shared.global [%0+512], [%1+57344], 16;"
                         ::"r"(stg + ((t + 2) & 3) * 1024 + lane * 16), "l"(src) : "memory");
            if (t < 13) asm volatile("cp.async.cg.shared.global [%0], [%1+917504], 16;\ncp.async.cg.shared.global [%0+512], [%1+974848], 16;"
                                     ::"r"(stg + ((t + 3) & 3) * 1024 + lane * 16), "l"(src) : "memory");
            cp_commit();
        }
        uint32_t v[16];
        const uint32_t r0 = stg + (t & 3) * 1024 + fl * 4, r1 = stg + ((t + 1) & 3) * 1024 + fl * 4;
#pragma unroll
        for (int i = 0; i < 8; i++) v[i] = lds32(r0 + i * 128);
#pragma unroll
        for (int i = 0; i < 8; i++) v[8 + i] = lds32(r1 + i * 128);
#pragma unroll
        for (int i = 0; i < 16; i++) v[i] = lds32(lut_a + v[i] * 128);
        uint4* dst = my_unit(t);
        stg128(dst, make_uint4(prmt(v[0], v[1], 0x5410), prmt(v[2], v[3], 0x5410), prmt(v[4], v[5], 0x5410), prmt(v[6], v[7], 0x5410)));
        if (t < 15) stg128(dst + 8 * BN, make_uint4(prmt(v[8], v[9], 0x5410), prmt(v[10], v[11], 0x5410), prmt(v[12], v[13], 0x5410), prmt(v[14], v[15], 0x5410)));
    };
    auto pace = [&](unsigned t) { unsigned c; do { asm volatile("mov.u32 %0, %%clock;" : "=r"(c)); } while (c - clk0 < t); };
    if (warp == 7) {
        TSW(7, 2); TSQ(1);
        if (lane == 0) {
            asm volatile("prefetch.tensormap [%0];" ::"l"(&tmx) : "memory");
            asm volatile("prefetch.tensormap [%0];" ::"l"(&tmx64) : "memory");
        }
        __syncwarp();
        TSW(7, 13); TSQ(3);
        pace(PX0);
        e_expect(bars + 8 * B_FULL, X_BYTES);
        issue_x(0, 0);
        TSQ(4);
        if (R1MODE == 4) {
            pace(PR1);
#pragma unroll
            for (int c = 0; c < 4; c++) load_blk(1, c);
            cp_commit();
        }
        target = ld_flag(myflags + 6);
        TSW(7, 1);
        pace(PR2);
        load_blk(2, 3);
        cp_commit();
        mbar_wait(bars + 8 * B_LUT);
        if (R1MODE == 4) {
            uint32_t c[32];
            cp_wait<1>();
            __syncwarp();
#pragma unroll
            for (int i = 0; i < 32; i++) c[i] = lds32(sbase + OFF_STG + (i >> 3) * 4096 + 1024 + (i & 7) * 128 + fl * 4);
#pragma unroll
            for (int i = 0; i < 32; i++) c[i] = lds32(sbase + OFF_LUT + (i >> 3) * 2048 + lane * 4 + c[i] * 128);
            uint4* dst = ptr_add(wscr, (uint32_t)(((g * 128 + 8 + mt) * BN + lane) * 16));
#pragma unroll
            for (int b = 0; b < 4; b++)
                stg128(dst + b * 32, make_uint4(prmt(c[8 * b], c[8 * b + 1], 0x5410), prmt(c[8 * b + 2], c[8 * b + 3], 0x5410),
                                                prmt(c[8 * b + 4], c[8 * b + 5], 0x5410), prmt(c[8 * b + 6], c[8 * b + 7], 0x5410)));
            TSW(7, 14);
        }
        target = (target | 7) + 1;
        if (PFX > 100) { pace(PFX); pf_x(PFXB + (g >> 2), mt * BM + (g & 3) * 64); }
        if (PX1 < 100000) { pace(PX1); issue_x(1, 1); }
        if (F2POS == 0) { cp_wait<0>(); __syncwarp(); foreign(2); }
        mbar_wait(bars + 8 * B_FULL);
        if (PX1 == 100000) issue_x(1, 1);
        if (PFX == 1) pf_x(PFXB + (g >> 2), mt * BM + (g & 3) * 64);
        if (F2POS == 1) { cp_wait<0>(); __syncwarp(); foreign(2); }
        if (W1BY == 7) {
            if (W1D) { unsigned c, c0; asm volatile("mov.u32 %0, %%clock;" : "=r"(c0)); do { asm volatile("mov.u32 %0, %%clock;" : "=r"(c)); } while (c - c0 < W1D); }
            e_bulk_p(1, bars + 8 * (B_FULL + 1), W_BYTES, sbase + OFF_W + W_BYTES, wgrp + 8 * BN);
            TSW(7, 4);
        }
        if (PX1 == 100001) issue_x(1, 1);
        if (F2POS == 2) { cp_wait<0>(); __syncwarp(); foreign(2); }
        if (PFX == 2) pf_x(PFXB + (g >> 2), mt * BM + (g & 3) * 64);
        TSW(7, 3);
    } else {
        if (wg == 1 && sl >= NOW) { pace(PSBASE + sl * PSTEP); load_slab(); }
        auto init_bars = [&]() {
            if (lane == 0) {
#pragma unroll
                for (int i = 0; i < 6; i++) {
                    const int b = 1 + warp * 6 + i;
                    if (b < B_SLAB) mbar_init(bars + 8 * b, b <= B_X15 + 1 ? 1 : 7);
                    if (b < B_XV || b == B_L) asm volatile("mbarrier.arrive.expect_tx.shared::cta.b64 _, [%0], %1;" ::"r"(bars + 8 * b), "r"(b == B_L ? X_BYTES / 2 + W_BYTES : X_BYTES + W_BYTES) : "memory");
                }
                asm volatile("fence.mbarrier_init.release.cluster;" ::: "memory");
            }
            __syncwarp();
        };
        init_bars();
        if (R1MODE != 4 || wg == 1) { pace(PR1); load_blk(1, warp); }
        cp_commit();
        TSW(0, 15);
        uint32_t lv[16], v[32], T[8];
        cp_wait<1>();
        __syncwarp();
#pragma unroll
        for (int i = 0; i < 16; i++) asm volatile("ld.shared.u16 %0, [%1];" : "=r"(lv[i]) : "r"(stg + i * 64 + fl * 2));
#pragma unroll
        for (int i = 0; i < 16; i++) lv[i] = lv[i] ? lv[i] : 0x8000u;
#pragma unroll
        for (int i = 0; i < 4; i++) {
            const uint32_t p01 = prmt(lv[4 * i], lv[4 * i + 1], 0x5140u), p23 = prmt(lv[4 * i + 2], lv[4 * i + 3], 0x5140u);
            T[i] = prmt(p01, p23, 0x5410u); T[4 + i] = prmt(p01, p23, 0x7632u);
        }
        TSW(0, 7);
#pragma unroll
        for (int i = 0; i < 16; i++) sts32(lut_a + i * 128, lv[i]);
        __syncwarp();
        e_arrive(bars + 8 * B_LUT);
        auto more_raw = [&](int j) {
            if (R2AT == j && wg == 1) { load_blk(2, warp); load_blk(2, warp - 4); cp_commit(); }
            if (R3AT == j && wg == 0) load_raw(3);
            if (R3W1 == j && wg == 1) load_raw(3);
        };
        auto own_task = [&](int t) {
            __syncwarp();
            uint32_t c[8];
#pragma unroll
            for (int i = 0; i < 8; i++) c[i] = lds32(stg + t * 1024 + fl * 4 + i * 128);
            uint4 o = lookup8_reg(c, T, two31);
            stg128(my_unit(t), o);
            if (t == 1) { TSW(4, 6); if (R1MODE != 4) TSW(0, 14); }
        };
        auto raw1_task = [&]() {
            if (wg == 1) cp_wait<(R2AT < 4) + (R3W1 < 4)>(); else cp_wait<(R3AT < 4)>();
            own_task(1);
        };
        auto piece_ld = [&](int j) {
            TSP(j * 8);
            mbar_wait(bars + 8 * (B_SLAB + j));
            TSP(j * 8 + 1);
#pragma unroll
            for (int i = 0; i < 16; i++) v[(j & 1) * 16 + i] = lds32(sbase + (j < 2 ? OFF_SLAB0 : OFF_SLAB2) + (j & 1) * SLAB_BYTES + i * (BN * 4) + (warp * 32 + fl) * 4);
            more_raw(j);
        };
        auto piece_st = [&](int j) {
            const uint32_t dst = sbase + OFF_W + j * 2 * CHUNK_BYTES + (warp * 32 + lane) * 16;
            sts128(dst, lookup8_reg(v + (j & 1) * 16, T, two31));
            sts128(dst + CHUNK_BYTES, lookup8_reg(v + (j & 1) * 16 + 8, T, two31));
            TSP(j * 8 + 2);
            TSW(PW, 8 + j);
        };
        if (R2AT < 0 && wg == 1) { pace(PR2); more_raw(R2AT); }
        piece_ld(0);
        if (PIPE & 1) piece_ld(1);
        piece_st(0);
        if (!(PIPE & 1)) piece_ld(1);
        if (PIPE & 2) piece_ld(2);
        piece_st(1);
        if (!(PIPE & 2)) piece_ld(2);
        if (PIPE & 4) piece_ld(3);
        piece_st(2);
        if (!(PIPE & 4)) piece_ld(3);
        if (R1MODE == 2 || (R1MODE == 3 && wg == 0)) raw1_task();
        piece_st(3);
        asm volatile("fence.proxy.async.shared::cta;" ::: "memory");
        TSP(27);
        __syncwarp();
        e_arrive(bars + 8 * B_FULL);
        if (R1MODE == 1 || (wg == 1 && R1MODE >= 3)) raw1_task();
        more_raw(4);
        if (wg == 1) {
            cp_wait<(R3W1 < 5)>();
            own_task(2);
            if (R34AT == 0) { if (R3W1 == 5) load_raw(3); load_raw(4); }
            mbar_wait(bars + 8 * B_LUT);
            foreign(2);
            if (R34AT == 1) { if (R3W1 == 5) load_raw(3); load_raw(4); }
        }
        TSW(4, 12);
    }

    float acc0[112], acc1[112];
    const uint64_t descA_hi = ((uint64_t)1 << 62) | ((uint64_t)(1024 >> 4) << 32) | ((uint64_t)1 << 16);
    const uint64_t descB_hi = ((uint64_t)(128 >> 4) << 32) | ((uint64_t)(CHUNK_BYTES >> 4) << 16);
    const uint32_t a16 = ((sbase & 0x3FFFF) >> 4) + wg * 1024 + (uint32_t)descA_hi, b16w = (((sbase + OFF_W) & 0x3FFFF) >> 4) + (uint32_t)descB_hi;
    auto dscA = [&](uint32_t lo) { return (descA_hi & 0xFFFFFFFF00000000ull) | lo; };
    auto dscB = [&](uint32_t lo) { return (descB_hi & 0xFFFFFFFF00000000ull) | lo; };
    uint32_t xo = 0, wo = 0, wo_prev = 2 * W_BYTES;
    const uint4* wnext = wgrp + 2 * 8 * BN;
    auto validate = [&](int t, uint32_t wofs) {
        constexpr int NV = VSPLIT == 1 ? 7 : 14;
        const uint32_t u = VSPLIT == 1 ? tid + wg * (W_BYTES / 32 - 128) : tid & 127;
        const uint32_t a = sbase + OFF_W + wofs + u * 16;
        for (int n = 0; n < 2000000; n++) {
            uint32_t m = 0xffffffffu;
#pragma unroll
            for (int i = 0; i < 7; i++) m = min(m, lds32(a + u * 16 + (lane >> 2) * 4 + i * 4096));
            if (__all_sync(0xffffffff, m != 0)) break;
            const uint4* src = ptr_add(wgrp, (uint32_t)((t * 8 * BN + (u & ~31) * 2 + lane) * 16));
#pragma unroll 1
            for (int i = 0; i < 14; i++) cp16(sbase + OFF_W + wofs + ((u & ~31) * 2 + lane + (i >> 1) * 256 + (i & 1) * 32) * 16, src + (i >> 1) * 256 + (i & 1) * 32);
            cp_commit();
            cp_wait<0>();
            asm volatile("fence.proxy.async.shared::cta;" ::: "memory");
            __syncwarp();
        }
    };
    auto batch = [&](int s, bool val) {
        if (val && s == 0) TSP(28);
        mbar_wait(bars + 8 * (B_FULL + s));
        if (val && s == 0) TSP(29);
        if (val && VSPLIT != 2 && wg == 0 && (unsigned)(s - 1) < NFAST) validate(s, wo);
        if (s + wg > 0) asm volatile("bar.sync %0, 256;" ::"r"(2 + wg) : "memory");
        TSW(0, 16 + s); TSW(4, 48 + s); TS8(16 + s);
        const uint32_t al = a16 + (xo >> 4), bl = b16w + (wo >> 4);
        wgmma_fence();
#pragma unroll
        for (int kk = 0; kk < 4; kk++) {
            const uint64_t db = dscB(bl + kk * (2 * CHUNK_BYTES >> 4));
            wgmma_m64n224k16(acc0, dscA(al + kk * 2), db, (s | kk) != 0);
            wgmma_m64n224k16(acc1, dscA(al + kk * 2 + (8192 >> 4)), db, (s | kk) != 0);
        }
        wgmma_commit();
        if (val && VSPLIT && wg == 1 && s < NFAST) { mbar_wait(bars + 8 * (B_FULL + s + 1)); validate(s + 1, 3 * W_BYTES - wo - wo_prev); }
        asm volatile("bar.arrive %0, 256;" ::"r"(3 - wg) : "memory");
        TSW(0, 32 + s); TSW(4, 64 + s);
    };
    auto advance = [&]() {
        wo_prev = wo;
        xo = xo == 2 * X_BYTES ? 0 : xo + X_BYTES;
        wo = wo == 2 * W_BYTES ? 0 : wo + W_BYTES;
        wnext += 8 * BN;
    };
    if (PEEL) batch(0, false);
#pragma unroll 1
    for (int s = 0; s < 9; s++) {
        if (!PEEL) batch(s, true);
        const uint32_t bs = bars + 8 * s;
        if (warp == 7) {
            const int fb = (int)(W_FLAG >> (4 * s)) & 15;
            unsigned* fp = ptr_add(myflags, fb * 4);
            unsigned fv = target;
            const int pb = round_batch(s);
            const uint32_t l1 = (L1_MASK >> s) & 1, l2 = (L2_MASK >> s) & 1;
            if (fb) fv = ld_flag(fp);
            else e_bulk_p(l1 && !pb, bs + 8 * (B_FULL + 2), W_BYTES, sbase + OFF_W + wo_prev, wnext);
            if (s == 0) {
                if (X2POS == 0) issue_x(2, 2);
                if (PFX == 3) pf_x(PFXB + (g >> 2), mt * BM + (g & 3) * 64);
                if (W2POS == 0) {
                    if (W2D) { unsigned c, c0; asm volatile("mov.u32 %0, %%clock;" : "=r"(c0)); do { asm volatile("mov.u32 %0, %%clock;" : "=r"(c)); } while (c - c0 < W2D); }
                    e_bulk_p(1, bs + 8 * (B_FULL + 2), W_BYTES, sbase + OFF_W + wo_prev, wnext);
                }
            }
            TSW(7, 112 + s);
            if (s == 0 && X2POS == 1) issue_x(2, 2);
            if (pb) {
                mbar_wait(bars + 8 * (B_DQ + pb));
                mbar_wait(bs + 8 * B_EMPTY);
                e_publish(ptr_add(myflags, pb * 4));
                e_bulk_p(l1, bs + 8 * (B_FULL + 2), W_BYTES, sbase + OFF_W + wo_prev, wnext);
            } else {
                if (fb) {
                    finish_poll(fp, fv, target);
                    e_bulk_p(l1, bs + 8 * (B_FULL + 2), W_BYTES, sbase + OFF_W + wo_prev, wnext);
                }
                mbar_wait(bs + 8 * B_EMPTY);
                if (s == W12_AT) {
                    issue_w(12, 3, B_WF);
                    e_bulk(bars + 8 * (B_WF + 3), W_BYTES / 2, sbase + OFF_LUT, wgrp + 15 * 8 * BN);
                }
            }
            wgmma_wait<0>();
            if (W2POS == 1) e_bulk_p(s == 0, bs + 8 * (B_FULL + 2), W_BYTES, sbase + OFF_W + wo_prev, wnext);
            e_bulk_p(l2, bs + 8 * (B_FULL + 3), W_BYTES, sbase + OFF_W + wo, wnext + 8 * BN);
            e_tma(bs + 8 * (B_FULL + 3), &tmx, sbase + OFF_X + xo, (s + 3) * BK, mt * BM);
            TSW(7, 96 + s);
        } else {
            if (s == 0) {
                if (wg == 0) {
                    if (R3AT > 4) load_raw(3);
                    if (R4W0 == 0) load_raw(4);
                    if (warp == W1BY) {
                        if (W1D) { unsigned c, c0; asm volatile("mov.u32 %0, %%clock;" : "=r"(c0)); do { asm volatile("mov.u32 %0, %%clock;" : "=r"(c)); } while (c - c0 < W1D); }
                        e_bulk_p(1, bars + 8 * (B_FULL + 1), W_BYTES, sbase + OFF_W + W_BYTES, wgrp + 8 * BN); TSW(3, 4);
                    }
                } else if (R34AT == 2) { if (R3W1 == 5) load_raw(3); load_raw(4); }
            }
            const int r = s + wg;
            if (R4W0 && r == 0) {
                cp_wait<0>();
                __syncwarp();
                stg128(my_unit(3), dequant8(stg + 3 * 1024 + fl * 4, lut_a));
                if (R4W0 == 2) mbar_wait(bars + 8 * (B_FULL + 1));
                load_raw(4); load_raw(5);
            } else if (wg == 0 && s < 2) coop(s + 3);
            else if (r < NROUNDS) { if (PAIR) coop2(2 * r + 1); else { coop(2 * r + 1); if (r < 7) coop(2 * r + 2); } }
            if (round_batch(r)) { __syncwarp(); e_arrive(bars + 8 * (B_DQ + round_batch(r))); }
            TSW(0, 80 + s);
            wgmma_wait<0>();
            if (warp == 3) e_arrive(bs + 8 * B_EMPTY);
            if (warp == 2 && (s & 3) == 1) pf_x(s + 4 + (g >> 2), mt * BM + (g & 3) * 64);
        }
        advance();
        if (PEEL) batch(s + 1, true);
    }
    auto rezero = [&]() {
        mbar_wait(bars + 8 * (B_FULL + 11));
#pragma unroll
        for (int t = 1; t <= NFAST; t++) stg128(my_unit(t), make_uint4(0, 0, 0, 0));
    };
    const int w4 = warp & 3;
    __nv_bfloat16* o = ptr_add(out, (uint32_t)(((mt * BM + wg * 128 + w4 * 16 + (lane >> 2)) * F_ + g * BN + (lane & 3) * 8) * 2));
    auto wofs = [](int st, int kk) -> uint32_t {
        return st < 15 ? OFF_W + (st == 11 ? 2 : st == 12 ? 3 : st - 13) * W_BYTES + kk * 2 * CHUNK_BYTES
                       : kk < 2 ? OFF_LUT + kk * 2 * CHUNK_BYTES : OFF_X + 2 * X_BYTES + (kk - 2) * 16384;
    };
    auto xofs = [](int st, int kk, int r) -> uint32_t {
        return (st == 11 ? 2 * X_BYTES + r * 8192 : ((st - 12) >> 1) * X_BYTES + (st & 1) * 8192) + kk * 32;
    };
    auto launder = [&]() { uint32_t b16 = (sbase & 0x3FFFF) >> 4; asm volatile("mov.u32 %0, %0;" : "+r"(b16)); return b16; };
    auto dA = [&](uint32_t b16, uint32_t ofs) { return (descA_hi & 0xFFFFFFFF00000000ull) | (uint64_t)(b16 + wg * 1024 + (ofs >> 4) + (uint32_t)descA_hi); };
    auto dB = [&](uint32_t b16, uint32_t ofs) { return (descB_hi & 0xFFFFFFFF00000000ull) | (uint64_t)(b16 + (ofs >> 4) + (uint32_t)descB_hi); };
    float p0[64], p1[32], p2[16];
    constexpr int PK0 = ASP < CSP ? ASP : CSP;
    uint32_t pk[(14 - PK0) * 4 + 1];
    auto split_acc1 = [&]() {
#pragma unroll
        for (int i = 0; i < 64; i++) asm volatile("add.f32 %0, %1, 0f00000000;" : "=f"(p0[i]) : "f"(acc1[i]));
#pragma unroll
        for (int i = 0; i < 32; i++) asm volatile("add.f32 %0, %1, 0f00000000;" : "=f"(p1[i]) : "f"(acc1[64 + i]));
#pragma unroll
        for (int i = 0; i < 16; i++) asm volatile("add.f32 %0, %1, 0f00000000;" : "=f"(p2[i]) : "f"(acc1[96 + i]));
    };
    {
        if (!PEEL) batch(9, false);
        if (warp == 7) {
            pf_x(13 + (g >> 2), mt * BM + (g & 3) * 64);
            mbar_wait(bars + 8 * (B_EMPTY + 9));
        } else if (ZPOS == 9) rezero();
        wgmma_wait<0>();
        if (warp == 3) e_arrive(bars + 8 * (B_EMPTY + 9));
        if (warp == 7) {
            issue_w(13, 0, B_WF + 1);
            e_expect(bars + 8 * B_XV, X_BYTES);
            issue_xv(12, 0, bars + 8 * B_XV); issue_xv(12, 1, bars + 8 * B_XV);
        }
        advance();
        batch(10, false);
        if (warp == 7) mbar_wait(bars + 8 * (B_EMPTY + 10)); else if (ZPOS == 10) rezero();
        wgmma_wait<0>();
        if (warp == 3) e_arrive(bars + 8 * (B_EMPTY + 10));
    }
    {
        mbar_wait(bars + 8 * (B_FULL + 11));
        asm volatile("bar.sync %0, 256;" ::"r"(2 + wg) : "memory");
        const uint32_t b16 = launder();
        wgmma_fence();
#pragma unroll
        for (int kk = 0; kk < 4; kk++) wgmma_m64n224k16(acc0, dA(b16, xofs(11, kk, 0)), dB(b16, wofs(11, kk)), 1);
        wgmma_commit();
        asm volatile("bar.arrive %0, 256;" ::"r"(3 - wg) : "memory");
        if (warp == 7) {
            issue_w(14, 1, B_WF + 2);
            e_expect(bars + 8 * (B_XV + 1), X_BYTES);
            issue_xv(13, 0, bars + 8 * (B_XV + 1)); issue_xv(13, 1, bars + 8 * (B_XV + 1));
            mbar_wait(bars + 8 * (B_EMPTY + 11));
        } else if (ZPOS == 11) rezero();
        if (!PLAG && FADDPOS == 0) split_acc1();
        wgmma_wait<0>();
        if (warp == 3) e_arrive(bars + 8 * (B_EMPTY + 11));
        if (warp == 7) {
            e_bulk(bars + 8 * (B_WF + 4), 2 * CHUNK_BYTES, sbase + wofs(15, 2), wgrp + (15 * 8 + 4) * BN);
            e_bulk(bars + 8 * (B_XV + 4), 2 * CHUNK_BYTES, sbase + wofs(15, 3), wgrp + (15 * 8 + 6) * BN);
        }
    }
    uint32_t af[80];
    const uint32_t lm = sbase + wg * 16384 + (w4 * 16 + (lane & 15)) * 128 + (((lane >> 4) ^ (lane & 7)) << 4);
    auto ldfrag = [&](int st) {
#pragma unroll
        for (int kk = 0; kk < 4; kk++) {
            uint32_t* r = af + ((st - 11) * 4 + kk) * 4;
            asm volatile("ldmatrix.sync.aligned.m8n8.x4.shared.b16 {%0,%1,%2,%3}, [%4];" : "=r"(r[0]), "=r"(r[1]), "=r"(r[2]), "=r"(r[3])
                         : "r"((lm ^ (kk << 5)) + xofs(st, 0, 1)) : "memory");
        }
    };
    {
        asm volatile("bar.sync %0, 256;" ::"r"(2 + wg) : "memory");
        TSK(0, 28); TSF(0);
        const uint32_t b16 = launder();
#pragma unroll
        for (int st = 12; st < 16; st++) {
            if (!(st & 1)) mbar_wait(bars + 8 * (B_XV + ((st - 12) >> 1)));
            mbar_wait(bars + 8 * (B_WF + st - 12));
            if (!(st & 1)) wgmma_fence();
#pragma unroll
            for (int kk = 0; kk < 4; kk++) {
                if (st == 15 && kk >= 2) mbar_wait(bars + 8 * (kk == 2 ? B_WF + 4 : B_XV + 4));
                wgmma_m64n224k16(acc0, dA(b16, xofs(st, kk, 0)), dB(b16, wofs(st, kk)), 1);
            }
            if (st & 1) wgmma_commit();
        }
        asm volatile("bar.arrive %0, 256;" ::"r"(3 - wg) : "memory");
        TSF(1);
        if (!PLAG && FADDPOS == 1) split_acc1();
        wgmma_wait<1>();
        if (w4 == 3) { e_expect(bars + 8 * (B_XV + 2 + wg), X_BYTES / 2); issue_xv(14, wg, bars + 8 * (B_XV + 2 + wg)); }
        wgmma_wait<0>();
        if (w4 == 3) { e_expect(bars + 8 * (B_X15 + wg), X_BYTES / 2); issue_xv(15, wg, bars + 8 * (B_X15 + wg)); }
        TSF(2); TS9(0);
        unsigned tb; asm volatile("mov.u32 %0, %%clock;" : "=r"(tb));
        auto pst = [&](unsigned t) { unsigned c; do { asm volatile("mov.u32 %0, %%clock;" : "=r"(c)); } while (c - tb < t); };
#pragma unroll
        for (int h = 0; h < PK0; h++) {
            if (PSTA && h >= PSF) pst((h - PSF + 1) * PSTA);
            store_half<0>(acc0, o, h);
            if (L11 == h) ldfrag(11);
            if (L12 == h) { mbar_wait(bars + 8 * (B_XV + 2 + wg)); ldfrag(12); if (L13) ldfrag(13); }
        }
#pragma unroll
        for (int h = PK0; h < 14; h++) pack_half(acc0, h, pk + (h - PK0) * 4);
#pragma unroll
        for (int h = PK0; h < (ASP > CSP ? ASP : CSP); h++) { if (PSTA && wg == (ASP > CSP ? 0 : 1)) pst((h - PSF + 1) * PSTA); store_packed(o, h, pk + (h - PK0) * 4, ASP > CSP ? wg ^ 1 : wg); }
        TSF(3);
    }
    {
        if (L11 < 0) ldfrag(11);
        TS9(5);
        asm volatile("bar.sync %0, 256;" ::"r"(2 + wg) : "memory");
        TSF(4);
        if (PLAG && wg == 1) {
            if (w4 < 2) e_bulk_p(1, bars + 8 * B_L, W_BYTES / 2, sbase + OFF_X + w4 * X_BYTES, wgrp + (10 * 8 + w4 * 4) * BN);
            else e_tma(bars + 8 * B_L, &tmx64, sbase + OFF_X + 2 * X_BYTES + 8192 + (w4 - 2) * 16384, 10 * BK, mt * BM + (w4 - 2) * 128 + 64);
        }
        const uint32_t b16 = launder();
#pragma unroll
        for (int st = 11; st < 16; st++) {
            wgmma_fence();
#pragma unroll
            for (int kk = 0; kk < 4; kk++) {
                const int i = (st - 11) * 4 + kk;
                wgmma_rs_n128(p0, af + i * 4, dB(b16, wofs(st, kk)));
                if (i == 0) TS9(1);
                constexpr int PD = L12 < 0 ? 1 : 2 + L13;
                if (kk == 0 && st + PD < 16) {
                    if (st == 11 && L12 < 0) mbar_wait(bars + 8 * (B_XV + 2 + wg));
                    if (st + PD == 14) mbar_wait(bars + 8 * (B_X15 + wg));
                    ldfrag(st + PD);
                }
                if (i % ISTEP == 0) {
                    const int h0 = ASP + i / ISTEP, h1 = CSP + i / ISTEP;
                    if (ASP == CSP) { if (h0 < 14) store_packed(o, h0, pk + (h0 - PK0) * 4, 1); }
                    else {
                        if (h0 < 14) store_packed(o, h0, pk + (h0 - PK0) * 4, wg ^ 1);
                        if (h1 < 14) store_packed(o, h1, pk + (h1 - PK0) * 4, wg);
                    }
                }
            }
        }
        wgmma_commit();
        asm volatile("bar.arrive %0, 256;" ::"r"(3 - wg) : "memory");
        TSF(5); TS9(2);
        wgmma_wait<0>();
        TSF(6); TS9(3);
        unsigned tb; asm volatile("mov.u32 %0, %%clock;" : "=r"(tb));
        auto pst = [&](unsigned t) { unsigned c; do { asm volatile("mov.u32 %0, %%clock;" : "=r"(c)); } while (c - tb < t); };
#pragma unroll
        for (int h = 0; h < (BSP > DSP ? BSP : DSP); h++) {
            if (h < BSP && h < DSP) { if (PSTB && wg == 0) pst(PSB0 + h * PSTB); store_half<64 * F_>(p0, o, h); }
            else if (wg == (BSP > DSP ? 0 : 1)) { if (PSTB && wg == 0) pst(PSB0 + h * PSTB); store_half<64 * F_>(p0, o, h); }
        }
        TSF(7);
    }
    {
        if (PLAG) mbar_wait(bars + 8 * B_L);
        asm volatile("bar.sync %0, 256;" ::"r"(2 + wg) : "memory");
        TSF(8);
        const uint32_t b16 = launder();
        wgmma_fence();
#pragma unroll
        for (int i = 0; i < 20; i++) {
            wgmma_rs_n64(p1, af + i * 4, dB(b16, wofs(11 + (i >> 2), i & 3) + 128 * 16));
            if (i % ISTEP2 == 0) {
                const int h0 = BSP + i / ISTEP2, h1 = DSP + i / ISTEP2;
                if (BSP == DSP) { if (h0 < 8) store_half<64 * F_>(p0, o, h0); }
                else {
                    if (h0 < 8) store_half<64 * F_>(p0, o, h0, wg ^ 1);
                    if (h1 < 8) store_half<64 * F_>(p0, o, h1, wg);
                }
            }
        }
        if (PLAG) {
#pragma unroll
            for (int kk = 0; kk < 4; kk++) wgmma_ss_n64(p1, dA(b16, xofs(11, kk, 1)), dB(b16, OFF_X + (kk >> 1) * X_BYTES + (kk & 1) * 2 * CHUNK_BYTES + 128 * 16));
        }
        wgmma_commit();
        if (PLAG) {
#pragma unroll
            for (int kk = 0; kk < 4; kk++) wgmma_ss_n32(p2, dA(b16, xofs(11, kk, 1)), dB(b16, OFF_X + (kk >> 1) * X_BYTES + (kk & 1) * 2 * CHUNK_BYTES + 192 * 16));
        }
#pragma unroll
        for (int i = 0; i < 20; i++) wgmma_rs_n32(p2, af + i * 4, dB(b16, wofs(11 + (i >> 2), i & 3) + 192 * 16));
        wgmma_commit();
        if (wg == 0) asm volatile("bar.arrive 3, 256;" ::: "memory");
        TSF(9);
        wgmma_wait<1>();
        TS9(4);
        store_tile<64 * F_ + 128, 0, 2>(p1, o);
        wgmma_wait<0>();
        TSK(4, 63); TSF(10);
        store_tile<64 * F_ + 192, 0, 1>(p2, o);
        TSK(4, 77); TSF(11);
    }
}

typedef CUresult (*EncodeTiledFn)(CUtensorMap*, CUtensorMapDataType, cuuint32_t, void*, const cuuint64_t*, const cuuint64_t*, const cuuint32_t*, const cuuint32_t*, CUtensorMapInterleave, CUtensorMapSwizzle, CUtensorMapL2promotion, CUtensorMapFloatOOBfill);

extern "C" void kernel_launch(void* const* d_in, const int* in_sizes, int n_in, void* d_out, int out_size) {
    static EncodeTiledFn enc = nullptr;
    static decltype(&fused_kernel<true>) kern = nullptr;
    static void *p_w = nullptr, *p_flags = nullptr, *p_prof = nullptr;
    if (!enc) {
        void* fn = nullptr; cudaDriverEntryPointQueryResult qr;
        cudaGetDriverEntryPoint("cuTensorMapEncodeTiled", &fn, cudaEnableDefault, &qr);
        enc = (EncodeTiledFn)fn;
        int dev = 0, rsv = 0;
        cudaGetDevice(&dev);
        cudaDeviceGetAttribute(&rsv, cudaDevAttrReservedSharedMemoryPerBlock, dev);
        kern = HARDBASE && rsv == 1024 ? fused_kernel<true> : fused_kernel<false>;
        cudaFuncSetAttribute(kern, cudaFuncAttributeMaxDynamicSharedMemorySize, SMEM_BYTES);
        cudaGetSymbolAddress(&p_w, g_w);
        cudaGetSymbolAddress(&p_flags, g_flags);
    }
    CUtensorMap tmx, tmx64, tmq;
    {
        cuuint64_t gdim[2] = {(cuuint64_t)F_, (cuuint64_t)D_};
        cuuint64_t gstr[1] = {(cuuint64_t)F_ * 4};
        cuuint32_t box[2] = {(cuuint32_t)BN, 16};
        cuuint32_t estr[2] = {1, 1};
        enc(&tmq, CU_TENSOR_MAP_DATA_TYPE_INT32, 2, d_in[1], gdim, gstr, box, estr, CU_TENSOR_MAP_INTERLEAVE_NONE,
            CU_TENSOR_MAP_SWIZZLE_NONE, CU_TENSOR_MAP_L2_PROMOTION_L2_128B, CU_TENSOR_MAP_FLOAT_OOB_FILL_NONE);
    }
    {
        cuuint64_t gdim[2] = {(cuuint64_t)D_, (cuuint64_t)S_};
        cuuint64_t gstr[1] = {(cuuint64_t)D_ * 2};
        cuuint32_t box[2] = {(cuuint32_t)BK, (cuuint32_t)BM};
        cuuint32_t estr[2] = {1, 1};
        enc(&tmx, CU_TENSOR_MAP_DATA_TYPE_BFLOAT16, 2, d_in[0], gdim, gstr, box, estr, CU_TENSOR_MAP_INTERLEAVE_NONE,
            CU_TENSOR_MAP_SWIZZLE_128B, XPROMO, CU_TENSOR_MAP_FLOAT_OOB_FILL_NONE);
        box[1] = 64;
        enc(&tmx64, CU_TENSOR_MAP_DATA_TYPE_BFLOAT16, 2, d_in[0], gdim, gstr, box, estr, CU_TENSOR_MAP_INTERLEAVE_NONE,
            CU_TENSOR_MAP_SWIZZLE_128B, XPROMO, CU_TENSOR_MAP_FLOAT_OOB_FILL_NONE);
    }
    kern<<<128, 256, SMEM_BYTES>>>((const int*)d_in[1], (const unsigned short*)d_in[2], (__nv_bfloat16*)d_out, (uint4*)p_w, (unsigned*)p_flags, 0x80000000u, tmq, tmx64, tmx
    );
    (void)p_prof;
}
```

```cpp
#include <cuda_runtime.h>
#include <cuda_bf16.h>
#include <cuda.h>
#include <stdint.h>
#include <stdio.h>

#define LA 2
#define XPROMO CU_TENSOR_MAP_L2_PROMOTION_L2_128B
#define CSPLIT 5
#define FADDPOS 1
#define BSPLIT 4
#define DSPLIT 4
#define FLAGPOS 1
#define RAW1POS 5
#define PIPE 6
#define PR1 1100
#define LK 1
#define PX0 1000
#define PX1 100000
#define R2AT 0
#define R3AT 3
#define R4AT 4
#define W1EARLY 1
#define PR2 1700
#define PSTEP 0
#define PSBASE 0
#define NOW 2
#define R34AT 0
#define R1MODE 1
#define ST2 1
#define PR34 3500
#define DEADT 300
#define PPOLL 2800
#define ALLONLY 0
#define X1POST 0
#define W3FIRST 1
#define W1BY 3
#define W1D 150
#define F2POS 1
#define W2POS 0
#define W2D 200
#define W3D 0
#define W4L2 0
#define R3W1 4
#define VGRAN 32
#define X2POS 0
#define VSPLIT 0
#define NF 4
#define PAIR 0
#define ZPOS 10
#define PFX 0
#define PFXB 2
#define ASP 10
#define CSP 10
#define BSP 8
#define DSP 6
#define ISTEP 2
#define ISTEP2 2
#define PEEL 1
#define ILV 0
#define R4W0 0
#define PLAG 0
#define PSTA 110
#define PSF 2
#define PSTB 110
#define PSB0 200
#define L11 2
#define L12 7
#define L13 0
#define NP2 0
#define NP2W 1
#define PSTD 100
#define HARDBASE 1

constexpr int S_ = 2048, D_ = 1024, F_ = 3584;
constexpr int BM = 256, BN = 224, BK = 64;
constexpr int X_BYTES = BM * BK * 2;
constexpr int W_BYTES = BN * BK * 2;
constexpr int CHUNK_BYTES = BN * 16;
constexpr int OFF_X = 0;
constexpr int OFF_W = 3 * X_BYTES;
constexpr int OFF_STG = OFF_W + 3 * W_BYTES;
constexpr int OFF_LUT = OFF_W + 4 * W_BYTES;
constexpr int OFF_BAR = OFF_LUT + 7 * 2048;
constexpr int OFF_PROF = OFF_BAR + 1024;
constexpr int SMEM_BYTES = OFF_PROF + 1024 + 1024;
constexpr int B_FULL = 0;
constexpr int B_XV = 12;
constexpr int B_WF = 17;
constexpr int B_EMPTY = 22;
constexpr int B_DQ = 34;
constexpr int B_SLAB = 42;
constexpr int B_L = 34;
constexpr int B_X15 = 35;
constexpr int B_LUT = 46;

__device__ __align__(1024) uint4 g_w[(size_t)F_ * D_ / 8];
__device__ __align__(128) unsigned g_flags[16 * 32];

__device__ __forceinline__ uint32_t smem_u32(const void* p) { return (uint32_t)__cvta_generic_to_shared(p); }
__device__ __forceinline__ void mbar_init(uint32_t bar, uint32_t cnt) { asm volatile("mbarrier.init.shared::cta.b64 [%0], %1;" ::"r"(bar), "r"(cnt) : "memory"); }
__device__ __forceinline__ void mbar_wait(uint32_t bar) {
    asm volatile("{\n.reg .pred p;\nWAIT_LOOP:\nmbarrier.try_wait.parity.shared::cta.b64 p, [%0], 0;\n@p bra WAIT_DONE;\nbra WAIT_LOOP;\nWAIT_DONE:\n}" ::"r"(bar) : "memory");
}
__device__ __forceinline__ void e_arrive(uint32_t bar) {
    asm volatile("{\n.reg .pred p;\nelect.sync _|p, 0xffffffff;\n@p mbarrier.arrive.shared::cta.b64 _, [%0];\n}" ::"r"(bar) : "memory");
}
__device__ __forceinline__ void e_expect(uint32_t bar, uint32_t bytes) {
    asm volatile("{\n.reg .pred p;\nelect.sync _|p, 0xffffffff;\n@p mbarrier.arrive.expect_tx.shared::cta.b64 _, [%0], %1;\n}" ::"r"(bar), "r"(bytes) : "memory");
}
__device__ __forceinline__ void e_tma(uint32_t bar, const CUtensorMap* tm, uint32_t d0, int x0, int y0) {
    asm volatile("{\n.reg .pred p;\nelect.sync _|p, 0xffffffff;\n"
                 "@p cp.async.bulk.tensor.2d.shared::cluster.global.mbarrier::complete_tx::bytes [%2], [%1, {%3, %4}], [%0];\n}"
                 ::"r"(bar), "l"(tm), "r"(d0), "r"(x0), "r"(y0) : "memory");
}
__device__ __forceinline__ void e_bulk(uint32_t bar, uint32_t bytes, uint32_t dst, const void* src) {
    asm volatile("{\n.reg .pred p;\nelect.sync _|p, 0xffffffff;\n"
                 "@p mbarrier.arrive.expect_tx.shared::cta.b64 _, [%0], %1;\n"
                 "@p cp.async.bulk.shared::cluster.global.mbarrier::complete_tx::bytes [%2], [%3], %1, [%0];\n}"
                 ::"r"(bar), "r"(bytes), "r"(dst), "l"(src) : "memory");
}
__device__ __forceinline__ void e_bulk_p(uint32_t on, uint32_t bar, uint32_t bytes, uint32_t dst, const void* src) {
    if (on) asm volatile("{\n.reg .pred p;\nelect.sync _|p, 0xffffffff;\n"
                         "@p cp.async.bulk.shared::cluster.global.mbarrier::complete_tx::bytes [%2], [%3], %1, [%0];\n}"
                         ::"r"(bar), "r"(bytes), "r"(dst), "l"(src) : "memory");
}
__device__ __forceinline__ void e_prefetch2d(const CUtensorMap* tm, int x, int y) {
    asm volatile("{\n.reg .pred p;\nelect.sync _|p, 0xffffffff;\n@p cp.async.bulk.prefetch.tensor.2d.L2.global [%0, {%1, %2}];\n}" ::"l"(tm), "r"(x), "r"(y) : "memory");
}
#define FASTREL 0
__device__ __forceinline__ void e_publish(unsigned* flag) {
    asm volatile("{\n.reg .pred p;\nelect.sync _|p, 0xffffffff;\n@p red.release.gpu.global.add.u32 [%0], 1;\n}" ::"l"(flag) : "memory");
}
__device__ __forceinline__ void e_red(unsigned* flag, unsigned v) {
    asm volatile("{\n.reg .pred p;\nelect.sync _|p, 0xffffffff;\n@p red.relaxed.gpu.global.add.u32 [%0], %1;\n}" ::"l"(flag), "r"(v) : "memory");
}
__device__ __forceinline__ bool mbar_test(uint32_t bar) {
    uint32_t r;
    asm volatile("{\n.reg .pred p;\nmbarrier.test_wait.parity.shared::cta.b64 p, [%1], 0;\nselp.u32 %0, 1, 0, p;\n}" : "=r"(r) : "r"(bar) : "memory");
    return __all_sync(0xffffffff, r != 0);
}
template <int V> struct IC { static constexpr int value = V; };
__device__ __forceinline__ unsigned ld_flag(const unsigned* f) { unsigned v; asm volatile("ld.relaxed.gpu.global.u32 %0, [%1];" : "=r"(v) : "l"(f) : "memory"); return v; }
__device__ __forceinline__ void finish_poll(const unsigned* f, unsigned v, unsigned target) {
    int n = 0;
    while (!__all_sync(0xffffffff, (int)(v - target) >= 0) && ++n < 4000000) v = ld_flag(f);
    asm volatile("fence.acquire.gpu;" ::: "memory");
    asm volatile("fence.proxy.async.global;" ::: "memory");
}
template <typename T> __device__ __forceinline__ T* ptr_add(T* base, uint32_t off) {
    uint64_t r;
    asm("{\n.reg .u32 l, h;\nmov.b64 {l, h}, %1;\nadd.cc.u32 l, l, %2;\naddc.u32 h, h, 0;\nmov.b64 %0, {l, h};\n}" : "=l"(r) : "l"(base), "r"(off));
    return (T*)r;
}
__device__ __forceinline__ void wgmma_fence() { asm volatile("wgmma.fence.sync.aligned;" ::: "memory"); }
__device__ __forceinline__ void wgmma_commit() { asm volatile("wgmma.commit_group.sync.aligned;" ::: "memory"); }
template <int N> __device__ __forceinline__ void wgmma_wait() { asm volatile("wgmma.wait_group.sync.aligned %0;" ::"n"(N) : "memory"); }
__device__ __forceinline__ void wgmma_m64n224k16(float (&d)[112], uint64_t da, uint64_t db, int scale_d) {
    asm volatile(
        "{\n.reg .pred p;\nsetp.ne.b32 p, %114, 0;\n"
        "wgmma.mma_async.sync.aligned.m64n224k16.f32.bf16.bf16 "
        "{%0, %1, %2, %3, %4, %5, %6, %7, %8, %9, %10, %11, %12, %13, %14, %15, "
        "%16, %17, %18, %19, %20, %21, %22, %23, %24, %25, %26, %27, %28, %29, %30, %31, "
        "%32, %33, %34, %35, %36, %37, %38, %39, %40, %41, %42, %43, %44, %45, %46, %47, "
        "%48, %49, %50, %51, %52, %53, %54, %55, %56, %57, %58, %59, %60, %61, %62, %63, "
        "%64, %65, %66, %67, %68, %69, %70, %71, %72, %73, %74, %75, %76, %77, %78, %79, "
        "%80, %81, %82, %83, %84, %85, %86, %87, %88, %89, %90, %91, %92, %93, %94, %95, "
        "%96, %97, %98, %99, %100, %101, %102, %103, %104, %105, %106, %107, %108, %109, %110, %111}, "
        "%112, %113, p, 1, 1, 0, 0;\n}\n"
        : "+f"(d[0]), "+f"(d[1]), "+f"(d[2]), "+f"(d[3]), "+f"(d[4]), "+f"(d[5]), "+f"(d[6]), "+f"(d[7]),
          "+f"(d[8]), "+f"(d[9]), "+f"(d[10]), "+f"(d[11]), "+f"(d[12]), "+f"(d[13]), "+f"(d[14]), "+f"(d[15]),
          "+f"(d[16]), "+f"(d[17]), "+f"(d[18]), "+f"(d[19]), "+f"(d[20]), "+f"(d[21]), "+f"(d[22]), "+f"(d[23]),
          "+f"(d[24]), "+f"(d[25]), "+f"(d[26]), "+f"(d[27]), "+f"(d[28]), "+f"(d[29]), "+f"(d[30]), "+f"(d[31]),
          "+f"(d[32]), "+f"(d[33]), "+f"(d[34]), "+f"(d[35]), "+f"(d[36]), "+f"(d[37]), "+f"(d[38]), "+f"(d[39]),
          "+f"(d[40]), "+f"(d[41]), "+f"(d[42]), "+f"(d[43]), "+f"(d[44]), "+f"(d[45]), "+f"(d[46]), "+f"(d[47]),
          "+f"(d[48]), "+f"(d[49]), "+f"(d[50]), "+f"(d[51]), "+f"(d[52]), "+f"(d[53]), "+f"(d[54]), "+f"(d[55]),
          "+f"(d[56]), "+f"(d[57]), "+f"(d[58]), "+f"(d[59]), "+f"(d[60]), "+f"(d[61]), "+f"(d[62]), "+f"(d[63]),
          "+f"(d[64]), "+f"(d[65]), "+f"(d[66]), "+f"(d[67]), "+f"(d[68]), "+f"(d[69]), "+f"(d[70]), "+f"(d[71]),
          "+f"(d[72]), "+f"(d[73]), "+f"(d[74]), "+f"(d[75]), "+f"(d[76]), "+f"(d[77]), "+f"(d[78]), "+f"(d[79]),
          "+f"(d[80]), "+f"(d[81]), "+f"(d[82]), "+f"(d[83]), "+f"(d[84]), "+f"(d[85]), "+f"(d[86]), "+f"(d[87]),
          "+f"(d[88]), "+f"(d[89]), "+f"(d[90]), "+f"(d[91]), "+f"(d[92]), "+f"(d[93]), "+f"(d[94]), "+f"(d[95]),
          "+f"(d[96]), "+f"(d[97]), "+f"(d[98]), "+f"(d[99]), "+f"(d[100]), "+f"(d[101]), "+f"(d[102]), "+f"(d[103]),
          "+f"(d[104]), "+f"(d[105]), "+f"(d[106]), "+f"(d[107]), "+f"(d[108]), "+f"(d[109]), "+f"(d[110]), "+f"(d[111])
        : "l"(da), "l"(db), "r"(scale_d));
}

__device__ __forceinline__ void wgmma_rs_n32(float (&d)[16], const uint32_t* a, uint64_t db) {
    asm volatile("wgmma.mma_async.sync.aligned.m64n32k16.f32.bf16.bf16 {%0, %1, %2, %3, %4, %5, %6, %7, %8, %9, %10, %11, %12, %13, %14, %15}, {%16, %17, %18, %19}, %20, 1, 1, 1, 0;"
        : "+f"(d[0]), "+f"(d[1]), "+f"(d[2]), "+f"(d[3]), "+f"(d[4]), "+f"(d[5]), "+f"(d[6]), "+f"(d[7]), "+f"(d[8]), "+f"(d[9]), "+f"(d[10]), "+f"(d[11]), "+f"(d[12]), "+f"(d[13]), "+f"(d[14]), "+f"(d[15])
        : "r"(a[0]), "r"(a[1]), "r"(a[2]), "r"(a[3]), "l"(db));
}
__device__ __forceinline__ void wgmma_ss_n32(float (&d)[16], uint64_t da, uint64_t db) {
    asm volatile("wgmma.mma_async.sync.aligned.m64n32k16.f32.bf16.bf16 {%0, %1, %2, %3, %4, %5, %6, %7, %8, %9, %10, %11, %12, %13, %14, %15}, %16, %17, 1, 1, 1, 0, 0;"
        : "+f"(d[0]), "+f"(d[1]), "+f"(d[2]), "+f"(d[3]), "+f"(d[4]), "+f"(d[5]), "+f"(d[6]), "+f"(d[7]), "+f"(d[8]), "+f"(d[9]), "+f"(d[10]), "+f"(d[11]), "+f"(d[12]), "+f"(d[13]), "+f"(d[14]), "+f"(d[15])
        : "l"(da), "l"(db));
}
__device__ __forceinline__ void wgmma_rs_n64(float (&d)[32], const uint32_t* a, uint64_t db) {
    asm volatile("wgmma.mma_async.sync.aligned.m64n64k16.f32.bf16.bf16 {%0, %1, %2, %3, %4, %5, %6, %7, %8, %9, %10, %11, %12, %13, %14, %15, %16, %17, %18, %19, %20, %21, %22, %23, %24, %25, %26, %27, %28, %29, %30, %31}, {%32, %33, %34, %35}, %36, 1, 1, 1, 0;"
        : "+f"(d[0]), "+f"(d[1]), "+f"(d[2]), "+f"(d[3]), "+f"(d[4]), "+f"(d[5]), "+f"(d[6]), "+f"(d[7]), "+f"(d[8]), "+f"(d[9]), "+f"(d[10]), "+f"(d[11]), "+f"(d[12]), "+f"(d[13]), "+f"(d[14]), "+f"(d[15]), "+f"(d[16]), "+f"(d[17]), "+f"(d[18]), "+f"(d[19]), "+f"(d[20]), "+f"(d[21]), "+f"(d[22]), "+f"(d[23]), "+f"(d[24]), "+f"(d[25]), "+f"(d[26]), "+f"(d[27]), "+f"(d[28]), "+f"(d[29]), "+f"(d[30]), "+f"(d[31])
        : "r"(a[0]), "r"(a[1]), "r"(a[2]), "r"(a[3]), "l"(db));
}
__device__ __forceinline__ void wgmma_ss_n64(float (&d)[32], uint64_t da, uint64_t db) {
    asm volatile("wgmma.mma_async.sync.aligned.m64n64k16.f32.bf16.bf16 {%0, %1, %2, %3, %4, %5, %6, %7, %8, %9, %10, %11, %12, %13, %14, %15, %16, %17, %18, %19, %20, %21, %22, %23, %24, %25, %26, %27, %28, %29, %30, %31}, %32, %33, 1, 1, 1, 0, 0;"
        : "+f"(d[0]), "+f"(d[1]), "+f"(d[2]), "+f"(d[3]), "+f"(d[4]), "+f"(d[5]), "+f"(d[6]), "+f"(d[7]), "+f"(d[8]), "+f"(d[9]), "+f"(d[10]), "+f"(d[11]), "+f"(d[12]), "+f"(d[13]), "+f"(d[14]), "+f"(d[15]), "+f"(d[16]), "+f"(d[17]), "+f"(d[18]), "+f"(d[19]), "+f"(d[20]), "+f"(d[21]), "+f"(d[22]), "+f"(d[23]), "+f"(d[24]), "+f"(d[25]), "+f"(d[26]), "+f"(d[27]), "+f"(d[28]), "+f"(d[29]), "+f"(d[30]), "+f"(d[31])
        : "l"(da), "l"(db));
}
__device__ __forceinline__ void wgmma_rs_n128(float (&d)[64], const uint32_t* a, uint64_t db) {
    asm volatile("wgmma.mma_async.sync.aligned.m64n128k16.f32.bf16.bf16 {%0, %1, %2, %3, %4, %5, %6, %7, %8, %9, %10, %11, %12, %13, %14, %15, %16, %17, %18, %19, %20, %21, %22, %23, %24, %25, %26, %27, %28, %29, %30, %31, %32, %33, %34, %35, %36, %37, %38, %39, %40, %41, %42, %43, %44, %45, %46, %47, %48, %49, %50, %51, %52, %53, %54, %55, %56, %57, %58, %59, %60, %61, %62, %63}, {%64, %65, %66, %67}, %68, 1, 1, 1, 0;"
        : "+f"(d[0]), "+f"(d[1]), "+f"(d[2]), "+f"(d[3]), "+f"(d[4]), "+f"(d[5]), "+f"(d[6]), "+f"(d[7]), "+f"(d[8]), "+f"(d[9]), "+f"(d[10]), "+f"(d[11]), "+f"(d[12]), "+f"(d[13]), "+f"(d[14]), "+f"(d[15]), "+f"(d[16]), "+f"(d[17]), "+f"(d[18]), "+f"(d[19]), "+f"(d[20]), "+f"(d[21]), "+f"(d[22]), "+f"(d[23]), "+f"(d[24]), "+f"(d[25]), "+f"(d[26]), "+f"(d[27]), "+f"(d[28]), "+f"(d[29]), "+f"(d[30]), "+f"(d[31]), "+f"(d[32]), "+f"(d[33]), "+f"(d[34]), "+f"(d[35]), "+f"(d[36]), "+f"(d[37]), "+f"(d[38]), "+f"(d[39]), "+f"(d[40]), "+f"(d[41]), "+f"(d[42]), "+f"(d[43]), "+f"(d[44]), "+f"(d[45]), "+f"(d[46]), "+f"(d[47]), "+f"(d[48]), "+f"(d[49]), "+f"(d[50]), "+f"(d[51]), "+f"(d[52]), "+f"(d[53]), "+f"(d[54]), "+f"(d[55]), "+f"(d[56]), "+f"(d[57]), "+f"(d[58]), "+f"(d[59]), "+f"(d[60]), "+f"(d[61]), "+f"(d[62]), "+f"(d[63])
        : "r"(a[0]), "r"(a[1]), "r"(a[2]), "r"(a[3]), "l"(db));
}
__device__ __forceinline__ void wgmma_ss_n128(float (&d)[64], uint64_t da, uint64_t db) {
    asm volatile("wgmma.mma_async.sync.aligned.m64n128k16.f32.bf16.bf16 {%0, %1, %2, %3, %4, %5, %6, %7, %8, %9, %10, %11, %12, %13, %14, %15, %16, %17, %18, %19, %20, %21, %22, %23, %24, %25, %26, %27, %28, %29, %30, %31, %32, %33, %34, %35, %36, %37, %38, %39, %40, %41, %42, %43, %44, %45, %46, %47, %48, %49, %50, %51, %52, %53, %54, %55, %56, %57, %58, %59, %60, %61, %62, %63}, %64, %65, 1, 1, 1, 0, 0;"
        : "+f"(d[0]), "+f"(d[1]), "+f"(d[2]), "+f"(d[3]), "+f"(d[4]), "+f"(d[5]), "+f"(d[6]), "+f"(d[7]), "+f"(d[8]), "+f"(d[9]), "+f"(d[10]), "+f"(d[11]), "+f"(d[12]), "+f"(d[13]), "+f"(d[14]), "+f"(d[15]), "+f"(d[16]), "+f"(d[17]), "+f"(d[18]), "+f"(d[19]), "+f"(d[20]), "+f"(d[21]), "+f"(d[22]), "+f"(d[23]), "+f"(d[24]), "+f"(d[25]), "+f"(d[26]), "+f"(d[27]), "+f"(d[28]), "+f"(d[29]), "+f"(d[30]), "+f"(d[31]), "+f"(d[32]), "+f"(d[33]), "+f"(d[34]), "+f"(d[35]), "+f"(d[36]), "+f"(d[37]), "+f"(d[38]), "+f"(d[39]), "+f"(d[40]), "+f"(d[41]), "+f"(d[42]), "+f"(d[43]), "+f"(d[44]), "+f"(d[45]), "+f"(d[46]), "+f"(d[47]), "+f"(d[48]), "+f"(d[49]), "+f"(d[50]), "+f"(d[51]), "+f"(d[52]), "+f"(d[53]), "+f"(d[54]), "+f"(d[55]), "+f"(d[56]), "+f"(d[57]), "+f"(d[58]), "+f"(d[59]), "+f"(d[60]), "+f"(d[61]), "+f"(d[62]), "+f"(d[63])
        : "l"(da), "l"(db));
}

__device__ __forceinline__ uint32_t pack_bf16(float lo, float hi) {
    uint32_t r; asm("cvt.rn.bf16x2.f32 %0, %1, %2;" : "=r"(r) : "f"(hi), "f"(lo)); return r;
}
__device__ __forceinline__ uint32_t lds32(uint32_t a) { uint32_t v; asm volatile("ld.shared.b32 %0, [%1];" : "=r"(v) : "r"(a)); return v; }
__device__ __forceinline__ void sts32(uint32_t a, uint32_t v) { asm volatile("st.shared.b32 [%0], %1;" ::"r"(a), "r"(v) : "memory"); }
__device__ __forceinline__ void sts128(uint32_t a, uint4 v) { asm volatile("st.shared.v4.b32 [%0], {%1,%2,%3,%4};" ::"r"(a), "r"(v.x), "r"(v.y), "r"(v.z), "r"(v.w) : "memory"); }
__device__ __forceinline__ void stg128(void* p, uint4 v) { asm volatile("st.global.v4.b32 [%0], {%1,%2,%3,%4};" ::"l"(p), "r"(v.x), "r"(v.y), "r"(v.z), "r"(v.w) : "memory"); }
__device__ __forceinline__ void cp16(uint32_t dst, const void* src) { asm volatile("cp.async.cg.shared.global [%0], [%1], 16;" ::"r"(dst), "l"(src) : "memory"); }
__device__ __forceinline__ void cp_commit() { asm volatile("cp.async.commit_group;" ::: "memory"); }
template <int N> __device__ __forceinline__ void cp_wait() { asm volatile("cp.async.wait_group %0;" ::"n"(N) : "memory"); }
__device__ __forceinline__ uint4 dequant8(uint32_t raw, uint32_t lut_a) {
    uint32_t v[8];
#pragma unroll
    for (int i = 0; i < 8; i++) v[i] = lds32(raw + i * 128);
#pragma unroll
    for (int i = 0; i < 8; i++) v[i] = lds32(lut_a + v[i] * 128);
    uint4 o;
    o.x = __byte_perm(v[0], v[1], 0x5410); o.y = __byte_perm(v[2], v[3], 0x5410);
    o.z = __byte_perm(v[4], v[5], 0x5410); o.w = __byte_perm(v[6], v[7], 0x5410);
    return o;
}
__device__ __forceinline__ uint32_t prmt(uint32_t a, uint32_t b, uint32_t c) { uint32_t r; asm("prmt.b32 %0, %1, %2, %3;" : "=r"(r) : "r"(a), "r"(b), "r"(c)); return r; }
__device__ __forceinline__ uint4 lookup8_reg(const uint32_t* c, const uint32_t (&T)[8], uint32_t two31) {
    uint32_t o[4];
#pragma unroll
    for (int h = 0; h < 2; h++) {
        const uint32_t sel = c[4 * h] + c[4 * h + 1] * 16 + c[4 * h + 2] * 256 + c[4 * h + 3] * 4096;
        const uint32_t s7 = sel & 0x7777u;
        uint32_t m;
        asm("lop3.b32 %0, %1, %2, 0x3210, 0xEA;" : "=r"(m) : "r"(__umulhi(sel, two31)), "r"(0x4444u));
        const uint32_t lo = prmt(prmt(T[0], T[1], s7), prmt(T[2], T[3], s7), m);
        const uint32_t hi = prmt(prmt(T[4], T[5], s7), prmt(T[6], T[7], s7), m);
        o[2 * h] = prmt(lo, hi, 0x5140u); o[2 * h + 1] = prmt(lo, hi, 0x7362u);
    }
    return make_uint4(o[0], o[1], o[2], o[3]);
}
template <int OFF, int G0, int G1, int N>
__device__ __forceinline__ void store_tile(const float (&acc)[N], __nv_bfloat16* o) {
#pragma unroll
    for (int G = G0; G < G1; G++) {
        uint4 v;
        v.x = pack_bf16(acc[G * 16 + 0], acc[G * 16 + 1]); v.y = pack_bf16(acc[G * 16 + 4], acc[G * 16 + 5]);
        v.z = pack_bf16(acc[G * 16 + 8], acc[G * 16 + 9]); v.w = pack_bf16(acc[G * 16 + 12], acc[G * 16 + 13]);
        stg128(o + OFF + G * 32, v);
        v.x = pack_bf16(acc[G * 16 + 2], acc[G * 16 + 3]); v.y = pack_bf16(acc[G * 16 + 6], acc[G * 16 + 7]);
        v.z = pack_bf16(acc[G * 16 + 10], acc[G * 16 + 11]); v.w = pack_bf16(acc[G * 16 + 14], acc[G * 16 + 15]);
        stg128(o + OFF + 8 * F_ + G * 32, v);
    }
}
template <int OFF, int N>
__device__ __forceinline__ void store_half(const float (&acc)[N], __nv_bfloat16* o, int H, int on = 1) {
    const int b = (H >> 1) * 16 + (H & 1) * 2;
    uint4 v;
    v.x = pack_bf16(acc[b + 0], acc[b + 1]); v.y = pack_bf16(acc[b + 4], acc[b + 5]);
    v.z = pack_bf16(acc[b + 8], acc[b + 9]); v.w = pack_bf16(acc[b + 12], acc[b + 13]);
    asm volatile("{\n.reg .pred p;\nsetp.ne.b32 p, %5, 0;\n@p st.global.v4.b32 [%0], {%1,%2,%3,%4};\n}"
                 ::"l"(o + OFF + (H & 1) * 8 * F_ + (H >> 1) * 32), "r"(v.x), "r"(v.y), "r"(v.z), "r"(v.w), "r"(on) : "memory");
}
template <int N>
__device__ __forceinline__ void pack_half(const float (&acc)[N], int H, uint32_t* r) {
    const int b = (H >> 1) * 16 + (H & 1) * 2;
#pragma unroll
    for (int i = 0; i < 4; i++) asm volatile("cvt.rn.bf16x2.f32 %0, %1, %2;" : "=r"(r[i]) : "f"(acc[b + 4 * i + 1]), "f"(acc[b + 4 * i]));
}
__device__ __forceinline__ void store_packed(__nv_bfloat16* o, int H, const uint32_t* r, int on) {
    asm volatile("{\n.reg .pred p;\nsetp.ne.b32 p, %5, 0;\n@p st.global.v4.b32 [%0], {%1,%2,%3,%4};\n}"
                 ::"l"(o + (H & 1) * 8 * F_ + (H >> 1) * 32), "r"(r[0]), "r"(r[1]), "r"(r[2]), "r"(r[3]), "r"(on) : "memory");
}
constexpr int NROUNDS = 8;
constexpr unsigned long long R_FIRST = 0xFDB97543ull, R_BATCH = 0x60050400ull, R_DOUBLE = 0x7C;
constexpr unsigned long long W_FLAG = 0x600504000ull;
constexpr unsigned L1_MASK = W4L2 ? 0x2A : 0x2E, L2_MASK = W4L2 ? 0x1EA : 0x1E8; constexpr int W12_AT = 8;
constexpr int NFAST = NF;
__device__ __forceinline__ int round_first(int r) { return (int)(R_FIRST >> (4 * r)) & 15; }
__device__ __forceinline__ int round_batch(int r) { return (int)(R_BATCH >> (4 * r)) & 15; }

#define TSK(w, i)
#define TSF(i)
#define TSP(i)
#define TSQ(i)
#define PW 0
#define TS9(i)
#define TS8(i)
#define TSW(w, i)

template <bool HARD>
__global__ void __launch_bounds__(256, 1)
fused_kernel(const int* __restrict__ qw, const unsigned short* __restrict__ lut, __nv_bfloat16* __restrict__ out,
             uint4* __restrict__ wscr, unsigned* __restrict__ flags, const uint32_t two31,
             const __grid_constant__ CUtensorMap tmq, const __grid_constant__ CUtensorMap tmx64, const __grid_constant__ CUtensorMap tmx
) {
    extern __shared__ uint8_t smem_raw[];
    const uint32_t sbase = HARD ? 1024u : (smem_u32(smem_raw) + 1023) & ~1023u;
    const uint32_t bars = sbase + OFF_BAR;
    const int tid = threadIdx.x, lane = tid & 31;
    const int mt = blockIdx.x & 7, g = blockIdx.x >> 3;
    unsigned clk0; asm volatile("mov.u32 %0, %%clock;" : "=r"(clk0));
    constexpr int SLAB_BYTES = 16 * BN * 4, OFF_SLAB0 = OFF_W + 2 * W_BYTES, OFF_SLAB2 = OFF_X + 2 * X_BYTES;
    const int warp = __shfl_sync(0xffffffff, tid >> 5, 0);
    if (tid >= 224) {
        asm volatile("{\n.reg .pred p;\nelect.sync _|p, 0xffffffff;\n"
                     "@p mbarrier.init.shared::cta.b64 [%0], 1;\n"
                     "@p fence.mbarrier_init.release.cluster;\n"
                     "@p mbarrier.arrive.expect_tx.shared::cta.b64 _, [%0], %1;\n"
                     "@p cp.async.bulk.tensor.2d.shared::cluster.global.mbarrier::complete_tx::bytes [%3], [%2, {%4, 0}], [%0];\n}"
                     ::"r"(bars + 8 * B_SLAB), "n"(SLAB_BYTES), "l"(&tmq), "r"(sbase + OFF_SLAB0), "r"(g * BN) : "memory");
    } else {
        const unsigned short* lp = ptr_add(lut, ((lane >> 2) * F_ + g * BN + (tid & ~31) + (lane & 3) * 8) * 2);
        asm volatile("cp.async.cg.shared.global [%0], [%1], 16;\ncp.async.cg.shared.global [%0+512], [%1+57344], 16;\ncp.async.commit_group;"
                     ::"r"(sbase + OFF_STG + (tid >> 5) * 4096 + lane * 16), "l"(lp) : "memory");
    }
    const int sl = warp - 3;
    auto load_slab = [&]() {
        e_tma(bars + 8 * (B_SLAB + sl), &tmq, sbase + (sl < 2 ? OFF_SLAB0 : OFF_SLAB2 - 2 * SLAB_BYTES) + sl * SLAB_BYTES, g * BN, sl * 16);
    };
    if (warp >= 4 && warp < 7) {
        asm volatile("{\n.reg .pred p;\nelect.sync _|p, 0xffffffff;\n"
                     "@p mbarrier.init.shared::cta.b64 [%0], 1;\n"
                     "@p fence.mbarrier_init.release.cluster;\n"
                     "@p mbarrier.arrive.expect_tx.shared::cta.b64 _, [%0], %1;\n}"
                     ::"r"(bars + 8 * (B_SLAB + sl)), "n"(SLAB_BYTES) : "memory");
        if (sl < NOW) load_slab();
    } else if (warp < 2) {
        asm volatile("{\n.reg .pred p;\nelect.sync _|p, 0xffffffff;\n"
                     "@p mbarrier.init.shared::cta.b64 [%0], %1;\n"
                     "@p fence.mbarrier_init.release.cluster;\n}" ::"r"(bars + 8 * (warp ? B_LUT : B_FULL)), "r"(8 - warp) : "memory");
    }
    asm volatile("bar.sync 1, 256;" ::: "memory");
    TSQ(0);
    const int wg = warp >> 2;

    const int fl = 8 * ((lane & 7) >> 1) + 2 * (lane >> 3) + (lane & 1);
    const uint32_t lut_a = sbase + OFF_LUT + warp * 2048 + lane * 4;
    const uint32_t stg = sbase + OFF_STG + warp * 4096;
    unsigned* myflags = flags + g * 32;
    const uint4* wgrp = wscr + (size_t)g * 128 * BN;
    unsigned target = 0;

    auto issue_x = [&](int s, int slot) {
        e_tma(bars + 8 * (B_FULL + s), &tmx, sbase + OFF_X + slot * X_BYTES, s * BK, mt * BM);
    };
    auto pf_x = [&](int s, int row0) { e_prefetch2d(&tmx64, s * BK, row0); };
    auto issue_xv = [&](int v, int w, uint32_t bar) {
        const uint32_t dst = sbase + OFF_X + (v & 1) * X_BYTES + w * 16384;
        const int k0 = (12 + 2 * (v & 1)) * BK, r0 = mt * BM + w * 128 + ((v >> 1) & 1) * 64;
        e_tma(bar, &tmx64, dst, k0, r0);
        e_tma(bar, &tmx64, dst + 8192, k0 + BK, r0);
    };
    auto issue_w = [&](int s, int slot, int bar) {
        e_bulk(bars + 8 * bar, W_BYTES, sbase + OFF_W + slot * W_BYTES, wgrp + s * 8 * BN);
    };
    auto load_raw = [&](int t) {
        if (t < 16) {
            const int* src = ptr_add(qw, (uint32_t)(((t * BK + mt * 8 + (lane >> 3)) * F_ + g * BN + warp * 32 + (lane & 7) * 4) * 4));
            asm volatile("cp.async.cg.shared.global [%0], [%1], 16;\ncp.async.cg.shared.global [%0+512], [%1+57344], 16;"
                         ::"r"(stg + (t & 3) * 1024 + lane * 16), "l"(src) : "memory");
        }
        cp_commit();
    };
    auto load_blk = [&](int t, int c) {
        const int* src = ptr_add(qw, (uint32_t)(((t * BK + mt * 8 + (lane >> 3)) * F_ + g * BN + c * 32 + (lane & 7) * 4) * 4));
        asm volatile("cp.async.cg.shared.global [%0], [%1], 16;\ncp.async.cg.shared.global [%0+512], [%1+57344], 16;"
                     ::"r"(sbase + OFF_STG + c * 4096 + t * 1024 + lane * 16), "l"(src) : "memory");
    };
    auto foreign = [&](int t) {
        const int c = warp ^ 4;
        stg128(ptr_add(wscr, (uint32_t)(((g * 128 + t * 8 + mt) * BN + c * 32 + lane) * 16)),
               dequant8(sbase + OFF_STG + c * 4096 + t * 1024 + fl * 4, sbase + OFF_LUT + c * 2048 + lane * 4));
        TSW(4, 5);
    };
    auto my_unit = [&](int t) { return ptr_add(wscr, (uint32_t)(((g * 128 + t * 8 + mt) * BN + warp * 32 + lane) * 16)); };
    auto coop = [&](int t) {
        cp_wait<LA - 1>();
        __syncwarp();
        load_raw(t + LA);
        stg128(my_unit(t), dequant8(stg + (t & 3) * 1024 + fl * 4, lut_a));

    };
    auto coop2 = [&](int t) {
        cp_wait<0>();
        __syncwarp();
        if (t < 14) {
            const int* src = ptr_add(qw, (uint32_t)((((t + 2) * BK + mt * 8 + (lane >> 3)) * F_ + g * BN + warp * 32 + (lane & 7) * 4) * 4));
            asm volatile("cp.async.cg.shared.global [%0], [%1], 16;\ncp.async.cg.shared.global [%0+512], [%1+57344], 16;"
                         ::"r"(stg + ((t + 2) & 3) * 1024 + lane * 16), "l"(src) : "memory");
            if (t < 13) asm volatile("cp.async.cg.shared.global [%0], [%1+917504], 16;\ncp.async.cg.shared.global [%0+512], [%1+974848], 16;"
                                     ::"r"(stg + ((t + 3) & 3) * 1024 + lane * 16), "l"(src) : "memory");
            cp_commit();
        }
        uint32_t v[16];
        const uint32_t r0 = stg + (t & 3) * 1024 + fl * 4, r1 = stg + ((t + 1) & 3) * 1024 + fl * 4;
#pragma unroll
        for (int i = 0; i < 8; i++) v[i] = lds32(r0 + i * 128);
#pragma unroll
        for (int i = 0; i < 8; i++) v[8 + i] = lds32(r1 + i * 128);
#pragma unroll
        for (int i = 0; i < 16; i++) v[i] = lds32(lut_a + v[i] * 128);
        uint4* dst = my_unit(t);
        stg128(dst, make_uint4(prmt(v[0], v[1], 0x5410), prmt(v[2], v[3], 0x5410), prmt(v[4], v[5], 0x5410), prmt(v[6], v[7], 0x5410)));
        if (t < 15) stg128(dst + 8 * BN, make_uint4(prmt(v[8], v[9], 0x5410), prmt(v[10], v[11], 0x5410), prmt(v[12], v[13], 0x5410), prmt(v[14], v[15], 0x5410)));
    };
    auto pace = [&](unsigned t) { unsigned c; do { asm volatile("mov.u32 %0, %%clock;" : "=r"(c)); } while (c - clk0 < t); };
    if (warp == 7) {
        TSW(7, 2); TSQ(1);
        if (lane == 0) {
            asm volatile("prefetch.tensormap [%0];" ::"l"(&tmx) : "memory");
            asm volatile("prefetch.tensormap [%0];" ::"l"(&tmx64) : "memory");
        }
        __syncwarp();
        TSW(7, 13); TSQ(3);
        pace(PX0);
        e_expect(bars + 8 * B_FULL, X_BYTES);
        issue_x(0, 0);
        TSQ(4);
        if (R1MODE == 4) {
            pace(PR1);
#pragma unroll
            for (int c = 0; c < 4; c++) load_blk(1, c);
            cp_commit();
        }
        target = ld_flag(myflags + 6);
        TSW(7, 1);
        pace(PR2);
        load_blk(2, 3);
        cp_commit();
        mbar_wait(bars + 8 * B_LUT);
        if (R1MODE == 4) {
            uint32_t c[32];
            cp_wait<1>();
            __syncwarp();
#pragma unroll
            for (int i = 0; i < 32; i++) c[i] = lds32(sbase + OFF_STG + (i >> 3) * 4096 + 1024 + (i & 7) * 128 + fl * 4);
#pragma unroll
            for (int i = 0; i < 32; i++) c[i] = lds32(sbase + OFF_LUT + (i >> 3) * 2048 + lane * 4 + c[i] * 128);
            uint4* dst = ptr_add(wscr, (uint32_t)(((g * 128 + 8 + mt) * BN + lane) * 16));
#pragma unroll
            for (int b = 0; b < 4; b++)
                stg128(dst + b * 32, make_uint4(prmt(c[8 * b], c[8 * b + 1], 0x5410), prmt(c[8 * b + 2], c[8 * b + 3], 0x5410),
                                                prmt(c[8 * b + 4], c[8 * b + 5], 0x5410), prmt(c[8 * b + 6], c[8 * b + 7], 0x5410)));
            TSW(7, 14);
        }
        target = (target | 7) + 1;
        if (PFX > 100) { pace(PFX); pf_x(PFXB + (g >> 2), mt * BM + (g & 3) * 64); }
        if (PX1 < 100000) { pace(PX1); issue_x(1, 1); }
        if (F2POS == 0) { cp_wait<0>(); __syncwarp(); foreign(2); }
        mbar_wait(bars + 8 * B_FULL);
        if (PX1 == 100000) issue_x(1, 1);
        if (PFX == 1) pf_x(PFXB + (g >> 2), mt * BM + (g & 3) * 64);
        if (F2POS == 1) { cp_wait<0>(); __syncwarp(); foreign(2); }
        if (W1BY == 7) {
            if (W1D) { unsigned c, c0; asm volatile("mov.u32 %0, %%clock;" : "=r"(c0)); do { asm volatile("mov.u32 %0, %%clock;" : "=r"(c)); } while (c - c0 < W1D); }
            e_bulk_p(1, bars + 8 * (B_FULL + 1), W_BYTES, sbase + OFF_W + W_BYTES, wgrp + 8 * BN);
            TSW(7, 4);
        }
        if (PX1 == 100001) issue_x(1, 1);
        if (F2POS == 2) { cp_wait<0>(); __syncwarp(); foreign(2); }
        if (PFX == 2) pf_x(PFXB + (g >> 2), mt * BM + (g & 3) * 64);
        TSW(7, 3);
    } else {
        if (wg == 1 && sl >= NOW) { pace(PSBASE + sl * PSTEP); load_slab(); }
        auto init_bars = [&]() {
            if (lane == 0) {
#pragma unroll
                for (int i = 0; i < 6; i++) {
                    const int b = 1 + warp * 6 + i;
                    if (b < B_SLAB) mbar_init(bars + 8 * b, b <= B_L + 3 ? 1 : 7);
                    if (b < B_XV || b == B_L || b == B_L + 3) asm volatile("mbarrier.arrive.expect_tx.shared::cta.b64 _, [%0], %1;" ::"r"(bars + 8 * b), "r"(b == B_L ? X_BYTES / 4 + W_BYTES : b == B_L + 3 ? X_BYTES / 4 : X_BYTES + W_BYTES) : "memory");
                }
                asm volatile("fence.mbarrier_init.release.cluster;" ::: "memory");
            }
            __syncwarp();
        };
        init_bars();
        if (R1MODE != 4 || wg == 1) { pace(PR1); load_blk(1, warp); }
        cp_commit();
        TSW(0, 15);
        uint32_t lv[16], v[32], T[8];
        cp_wait<1>();
        __syncwarp();
#pragma unroll
        for (int i = 0; i < 16; i++) asm volatile("ld.shared.u16 %0, [%1];" : "=r"(lv[i]) : "r"(stg + i * 64 + fl * 2));
#pragma unroll
        for (int i = 0; i < 16; i++) lv[i] = lv[i] ? lv[i] : 0x8000u;
#pragma unroll
        for (int i = 0; i < 4; i++) {
            const uint32_t p01 = prmt(lv[4 * i], lv[4 * i + 1], 0x5140u), p23 = prmt(lv[4 * i + 2], lv[4 * i + 3], 0x5140u);
            T[i] = prmt(p01, p23, 0x5410u); T[4 + i] = prmt(p01, p23, 0x7632u);
        }
        TSW(0, 7);
#pragma unroll
        for (int i = 0; i < 16; i++) sts32(lut_a + i * 128, lv[i]);
        __syncwarp();
        e_arrive(bars + 8 * B_LUT);
        auto more_raw = [&](int j) {
            if (R2AT == j && wg == 1) { load_blk(2, warp); load_blk(2, warp - 4); cp_commit(); }
            if (R3AT == j && wg == 0) load_raw(3);
            if (R3W1 == j && wg == 1) load_raw(3);
        };
        auto own_task = [&](int t) {
            __syncwarp();
            uint32_t c[8];
#pragma unroll
            for (int i = 0; i < 8; i++) c[i] = lds32(stg + t * 1024 + fl * 4 + i * 128);
            uint4 o = lookup8_reg(c, T, two31);
            stg128(my_unit(t), o);
            if (t == 1) { TSW(4, 6); if (R1MODE != 4) TSW(0, 14); }
        };
        auto raw1_task = [&]() {
            if (wg == 1) cp_wait<(R2AT < 4) + (R3W1 < 4)>(); else cp_wait<(R3AT < 4)>();
            own_task(1);
        };
        auto piece_ld = [&](int j) {
            TSP(j * 8);
            mbar_wait(bars + 8 * (B_SLAB + j));
            TSP(j * 8 + 1);
#pragma unroll
            for (int i = 0; i < 16; i++) v[(j & 1) * 16 + i] = lds32(sbase + (j < 2 ? OFF_SLAB0 : OFF_SLAB2) + (j & 1) * SLAB_BYTES + i * (BN * 4) + (warp * 32 + fl) * 4);
            more_raw(j);
        };
        auto piece_st = [&](int j) {
            const uint32_t dst = sbase + OFF_W + j * 2 * CHUNK_BYTES + (warp * 32 + lane) * 16;
            sts128(dst, lookup8_reg(v + (j & 1) * 16, T, two31));
            sts128(dst + CHUNK_BYTES, lookup8_reg(v + (j & 1) * 16 + 8, T, two31));
            TSP(j * 8 + 2);
            TSW(PW, 8 + j);
        };
        if (R2AT < 0 && wg == 1) { pace(PR2); more_raw(R2AT); }
        piece_ld(0);
        if (PIPE & 1) piece_ld(1);
        piece_st(0);
        if (!(PIPE & 1)) piece_ld(1);
        if (PIPE & 2) piece_ld(2);
        piece_st(1);
        if (!(PIPE & 2)) piece_ld(2);
        if (PIPE & 4) piece_ld(3);
        piece_st(2);
        if (!(PIPE & 4)) piece_ld(3);
        if (R1MODE == 2 || (R1MODE == 3 && wg == 0)) raw1_task();
        piece_st(3);
        asm volatile("fence.proxy.async.shared::cta;" ::: "memory");
        TSP(27);
        __syncwarp();
        e_arrive(bars + 8 * B_FULL);
        if (R1MODE == 1 || (wg == 1 && R1MODE >= 3)) raw1_task();
        more_raw(4);
        if (wg == 1) {
            cp_wait<(R3W1 < 5)>();
            own_task(2);
            if (R34AT == 0) { if (R3W1 == 5) load_raw(3); load_raw(4); }
            mbar_wait(bars + 8 * B_LUT);
            foreign(2);
            if (R34AT == 1) { if (R3W1 == 5) load_raw(3); load_raw(4); }
        }
        TSW(4, 12);
    }

    float acc0[112], acc1[112];
    const uint64_t descA_hi = ((uint64_t)1 << 62) | ((uint64_t)(1024 >> 4) << 32) | ((uint64_t)1 << 16);
    const uint64_t descB_hi = ((uint64_t)(128 >> 4) << 32) | ((uint64_t)(CHUNK_BYTES >> 4) << 16);
    const uint32_t a16 = ((sbase & 0x3FFFF) >> 4) + wg * 1024 + (uint32_t)descA_hi, b16w = (((sbase + OFF_W) & 0x3FFFF) >> 4) + (uint32_t)descB_hi;
    auto dscA = [&](uint32_t lo) { return (descA_hi & 0xFFFFFFFF00000000ull) | lo; };
    auto dscB = [&](uint32_t lo) { return (descB_hi & 0xFFFFFFFF00000000ull) | lo; };
    uint32_t xo = 0, wo = 0, wo_prev = 2 * W_BYTES;
    const uint4* wnext = wgrp + 2 * 8 * BN;
    auto validate = [&](int t, uint32_t wofs) {
        constexpr int NV = VSPLIT == 1 ? 7 : 14;
        const uint32_t u = VSPLIT == 1 ? tid + wg * (W_BYTES / 32 - 128) : tid & 127;
        const uint32_t a = sbase + OFF_W + wofs + u * 16;
        for (int n = 0; n < 2000000; n++) {
            uint32_t m = 0xffffffffu;
#pragma unroll
            for (int i = 0; i < 7; i++) m = min(m, lds32(a + u * 16 + (lane >> 2) * 4 + i * 4096));
            if (__all_sync(0xffffffff, m != 0)) break;
            const uint4* src = ptr_add(wgrp, (uint32_t)((t * 8 * BN + (u & ~31) * 2 + lane) * 16));
#pragma unroll 1
            for (int i = 0; i < 14; i++) cp16(sbase + OFF_W + wofs + ((u & ~31) * 2 + lane + (i >> 1) * 256 + (i & 1) * 32) * 16, src + (i >> 1) * 256 + (i & 1) * 32);
            cp_commit();
            cp_wait<0>();
            asm volatile("fence.proxy.async.shared::cta;" ::: "memory");
            __syncwarp();
        }
    };
    auto batch = [&](int s, bool val) {
        if (val && s == 0) TSP(28);
        mbar_wait(bars + 8 * (B_FULL + s));
        if (val && s == 0) TSP(29);
        if (val && VSPLIT != 2 && wg == 0 && (unsigned)(s - 1) < NFAST) validate(s, wo);
        if (s + wg > 0) asm volatile("bar.sync %0, 256;" ::"r"(2 + wg) : "memory");
        TSW(0, 16 + s); TSW(4, 48 + s); TS8(16 + s);
        const uint32_t al = a16 + (xo >> 4), bl = b16w + (wo >> 4);
        wgmma_fence();
#pragma unroll
        for (int kk = 0; kk < 4; kk++) {
            const uint64_t db = dscB(bl + kk * (2 * CHUNK_BYTES >> 4));
            wgmma_m64n224k16(acc0, dscA(al + kk * 2), db, (s | kk) != 0);
            wgmma_m64n224k16(acc1, dscA(al + kk * 2 + (8192 >> 4)), db, (s | kk) != 0);
        }
        wgmma_commit();
        if (val && VSPLIT && wg == 1 && s < NFAST) { mbar_wait(bars + 8 * (B_FULL + s + 1)); validate(s + 1, 3 * W_BYTES - wo - wo_prev); }
        asm volatile("bar.arrive %0, 256;" ::"r"(3 - wg) : "memory");
        TSW(0, 32 + s); TSW(4, 64 + s);
    };
    auto advance = [&]() {
        wo_prev = wo;
        xo = xo == 2 * X_BYTES ? 0 : xo + X_BYTES;
        wo = wo == 2 * W_BYTES ? 0 : wo + W_BYTES;
        wnext += 8 * BN;
    };
    if (PEEL) batch(0, false);
#pragma unroll 1
    for (int s = 0; s < 9; s++) {
        if (!PEEL) batch(s, true);
        const uint32_t bs = bars + 8 * s;
        if (warp == 7) {
            const int fb = (int)(W_FLAG >> (4 * s)) & 15;
            unsigned* fp = ptr_add(myflags, fb * 4);
            unsigned fv = target;
            const int pb = round_batch(s);
            const uint32_t l1 = (L1_MASK >> s) & 1, l2 = (L2_MASK >> s) & 1;
            if (fb) fv = ld_flag(fp);
            else e_bulk_p(l1 && !pb, bs + 8 * (B_FULL + 2), W_BYTES, sbase + OFF_W + wo_prev, wnext);
            if (s == 0) {
                if (X2POS == 0) issue_x(2, 2);
                if (PFX == 3) pf_x(PFXB + (g >> 2), mt * BM + (g & 3) * 64);
                if (W2POS == 0) {
                    if (W2D) { unsigned c, c0; asm volatile("mov.u32 %0, %%clock;" : "=r"(c0)); do { asm volatile("mov.u32 %0, %%clock;" : "=r"(c)); } while (c - c0 < W2D); }
                    e_bulk_p(1, bs + 8 * (B_FULL + 2), W_BYTES, sbase + OFF_W + wo_prev, wnext);
                }
            }
            TSW(7, 112 + s);
            if (s == 0 && X2POS == 1) issue_x(2, 2);
            if (pb) {
                mbar_wait(bars + 8 * (B_DQ + pb));
                mbar_wait(bs + 8 * B_EMPTY);
                e_publish(ptr_add(myflags, pb * 4));
                e_bulk_p(l1, bs + 8 * (B_FULL + 2), W_BYTES, sbase + OFF_W + wo_prev, wnext);
            } else {
                if (fb) {
                    finish_poll(fp, fv, target);
                    e_bulk_p(l1, bs + 8 * (B_FULL + 2), W_BYTES, sbase + OFF_W + wo_prev, wnext);
                }
                mbar_wait(bs + 8 * B_EMPTY);
                if (s == W12_AT) {
                    issue_w(12, 3, B_WF);
                    e_bulk(bars + 8 * (B_WF + 3), W_BYTES / 2, sbase + OFF_LUT, wgrp + 15 * 8 * BN);
                }
            }
            wgmma_wait<0>();
            if (W2POS == 1) e_bulk_p(s == 0, bs + 8 * (B_FULL + 2), W_BYTES, sbase + OFF_W + wo_prev, wnext);
            e_bulk_p(l2, bs + 8 * (B_FULL + 3), W_BYTES, sbase + OFF_W + wo, wnext + 8 * BN);
            e_tma(bs + 8 * (B_FULL + 3), &tmx, sbase + OFF_X + xo, (s + 3) * BK, mt * BM);
            TSW(7, 96 + s);
        } else {
            if (s == 0) {
                if (wg == 0) {
                    if (R3AT > 4) load_raw(3);
                    if (R4W0 == 0) load_raw(4);
                    if (warp == W1BY) {
                        if (W1D) { unsigned c, c0; asm volatile("mov.u32 %0, %%clock;" : "=r"(c0)); do { asm volatile("mov.u32 %0, %%clock;" : "=r"(c)); } while (c - c0 < W1D); }
                        e_bulk_p(1, bars + 8 * (B_FULL + 1), W_BYTES, sbase + OFF_W + W_BYTES, wgrp + 8 * BN); TSW(3, 4);
                    }
                } else if (R34AT == 2) { if (R3W1 == 5) load_raw(3); load_raw(4); }
            }
            const int r = s + wg;
            if (R4W0 && r == 0) {
                cp_wait<0>();
                __syncwarp();
                stg128(my_unit(3), dequant8(stg + 3 * 1024 + fl * 4, lut_a));
                if (R4W0 == 2) mbar_wait(bars + 8 * (B_FULL + 1));
                load_raw(4); load_raw(5);
            } else if (wg == 0 && s < 2) coop(s + 3);
            else if (r < NROUNDS) { if (PAIR) coop2(2 * r + 1); else { coop(2 * r + 1); if (r < 7) coop(2 * r + 2); } }
            if (round_batch(r)) { __syncwarp(); e_arrive(bars + 8 * (B_DQ + round_batch(r))); }
            TSW(0, 80 + s);
            wgmma_wait<0>();
            if (warp == 3) e_arrive(bs + 8 * B_EMPTY);
            if (warp == 2 && (s & 3) == 1) pf_x(s + 4 + (g >> 2), mt * BM + (g & 3) * 64);
        }
        advance();
        if (PEEL) batch(s + 1, true);
    }
    auto rezero = [&]() {
        mbar_wait(bars + 8 * (B_FULL + 11));
#pragma unroll
        for (int t = 1; t <= NFAST; t++) stg128(my_unit(t), make_uint4(0, 0, 0, 0));
    };
    const int w4 = warp & 3;
    __nv_bfloat16* o = ptr_add(out, (uint32_t)(((mt * BM + wg * 128 + w4 * 16 + (lane >> 2)) * F_ + g * BN + (lane & 3) * 8) * 2));
    auto wofs = [](int st, int kk) -> uint32_t {
        return st < 15 ? OFF_W + (st == 11 ? 2 : st == 12 ? 3 : st - 13) * W_BYTES + kk * 2 * CHUNK_BYTES
                       : kk < 2 ? OFF_LUT + kk * 2 * CHUNK_BYTES : OFF_X + 2 * X_BYTES + (kk - 2) * 16384;
    };
    auto xofs = [](int st, int kk, int r) -> uint32_t {
        return (st == 11 ? 2 * X_BYTES + r * 8192 : ((st - 12) >> 1) * X_BYTES + (st & 1) * 8192) + kk * 32;
    };
    auto launder = [&]() { uint32_t b16 = (sbase & 0x3FFFF) >> 4; asm volatile("mov.u32 %0, %0;" : "+r"(b16)); return b16; };
    auto dA = [&](uint32_t b16, uint32_t ofs) { return (descA_hi & 0xFFFFFFFF00000000ull) | (uint64_t)(b16 + wg * 1024 + (ofs >> 4) + (uint32_t)descA_hi); };
    auto dB = [&](uint32_t b16, uint32_t ofs) { return (descB_hi & 0xFFFFFFFF00000000ull) | (uint64_t)(b16 + (ofs >> 4) + (uint32_t)descB_hi); };
    float p0[64], p1[32], p2[16];
    constexpr int PK0 = ASP < CSP ? ASP : CSP;
    uint32_t pk[(14 - PK0) * 4 + 1];
    auto split_acc1 = [&]() {
#pragma unroll
        for (int i = 0; i < 64; i++) asm volatile("add.f32 %0, %1, 0f00000000;" : "=f"(p0[i]) : "f"(acc1[i]));
#pragma unroll
        for (int i = 0; i < 32; i++) asm volatile("add.f32 %0, %1, 0f00000000;" : "=f"(p1[i]) : "f"(acc1[64 + i]));
#pragma unroll
        for (int i = 0; i < 16; i++) asm volatile("add.f32 %0, %1, 0f00000000;" : "=f"(p2[i]) : "f"(acc1[96 + i]));
    };
    {
        if (!PEEL) batch(9, false);
        if (warp == 7) {
            pf_x(13 + (g >> 2), mt * BM + (g & 3) * 64);
            mbar_wait(bars + 8 * (B_EMPTY + 9));
        } else if (ZPOS == 9) rezero();
        wgmma_wait<0>();
        if (warp == 3) e_arrive(bars + 8 * (B_EMPTY + 9));
        if (warp == 7) {
            issue_w(13, 0, B_WF + 1);
            e_expect(bars + 8 * B_XV, X_BYTES);
            issue_xv(12, 0, bars + 8 * B_XV); issue_xv(12, 1, bars + 8 * B_XV);
        }
        advance();
        batch(10, false);
        if (warp == 7) mbar_wait(bars + 8 * (B_EMPTY + 10)); else if (ZPOS == 10) rezero();
        wgmma_wait<0>();
        if (warp == 3) e_arrive(bars + 8 * (B_EMPTY + 10));
    }
    {
        mbar_wait(bars + 8 * (B_FULL + 11));
        asm volatile("bar.sync %0, 256;" ::"r"(2 + wg) : "memory");
        const uint32_t b16 = launder();
        wgmma_fence();
#pragma unroll
        for (int kk = 0; kk < 4; kk++) wgmma_m64n224k16(acc0, dA(b16, xofs(11, kk, 0)), dB(b16, wofs(11, kk)), 1);
        wgmma_commit();
        asm volatile("bar.arrive %0, 256;" ::"r"(3 - wg) : "memory");
        if (warp == 7) {
            issue_w(14, 1, B_WF + 2);
            e_expect(bars + 8 * (B_XV + 1), X_BYTES);
            issue_xv(13, 0, bars + 8 * (B_XV + 1)); issue_xv(13, 1, bars + 8 * (B_XV + 1));
            mbar_wait(bars + 8 * (B_EMPTY + 11));
        } else if (ZPOS == 11) rezero();
        if (!PLAG && FADDPOS == 0) split_acc1();
        wgmma_wait<0>();
        if (warp == 3) e_arrive(bars + 8 * (B_EMPTY + 11));
        if (warp == 7) {
            e_bulk(bars + 8 * (B_WF + 4), 2 * CHUNK_BYTES, sbase + wofs(15, 2), wgrp + (15 * 8 + 4) * BN);
            e_bulk(bars + 8 * (B_XV + 4), 2 * CHUNK_BYTES, sbase + wofs(15, 3), wgrp + (15 * 8 + 6) * BN);
        }
    }
    uint32_t af[80];
    const uint32_t lm = sbase + wg * 16384 + (w4 * 16 + (lane & 15)) * 128 + (((lane >> 4) ^ (lane & 7)) << 4);
    auto ldfrag = [&](int st) {
#pragma unroll
        for (int kk = 0; kk < 4; kk++) {
            uint32_t* r = af + ((st - 11) * 4 + kk) * 4;
            asm volatile("ldmatrix.sync.aligned.m8n8.x4.shared.b16 {%0,%1,%2,%3}, [%4];" : "=r"(r[0]), "=r"(r[1]), "=r"(r[2]), "=r"(r[3])
                         : "r"((lm ^ (kk << 5)) + xofs(st, 0, 1)) : "memory");
        }
    };
    {
        asm volatile("bar.sync %0, 256;" ::"r"(2 + wg) : "memory");
        TSK(0, 28); TSF(0);
        const uint32_t b16 = launder();
#pragma unroll
        for (int st = 12; st < 16; st++) {
            if (!(st & 1)) mbar_wait(bars + 8 * (B_XV + ((st - 12) >> 1)));
            mbar_wait(bars + 8 * (B_WF + st - 12));
            if (!(st & 1)) wgmma_fence();
#pragma unroll
            for (int kk = 0; kk < 4; kk++) {
                if (st == 15 && kk >= 2) mbar_wait(bars + 8 * (kk == 2 ? B_WF + 4 : B_XV + 4));
                wgmma_m64n224k16(acc0, dA(b16, xofs(st, kk, 0)), dB(b16, wofs(st, kk)), 1);
            }
            if (st & 1) wgmma_commit();
        }
        asm volatile("bar.arrive %0, 256;" ::"r"(3 - wg) : "memory");
        TSF(1);
        if (!PLAG && FADDPOS == 1) split_acc1();
        wgmma_wait<1>();
        if (w4 == 3) { e_expect(bars + 8 * (B_XV + 2 + wg), X_BYTES / 2); issue_xv(14, wg, bars + 8 * (B_XV + 2 + wg)); }
        wgmma_wait<0>();
        if (w4 == 3) { e_expect(bars + 8 * (B_X15 + wg), X_BYTES / 2); issue_xv(15, wg, bars + 8 * (B_X15 + wg)); }
        TSF(2); TS9(0);
        unsigned tb; asm volatile("mov.u32 %0, %%clock;" : "=r"(tb));
        auto pst = [&](unsigned t) { unsigned c; do { asm volatile("mov.u32 %0, %%clock;" : "=r"(c)); } while (c - tb < t); };
#pragma unroll
        for (int h = 0; h < PK0; h++) {
            if (PSTA && h >= PSF) pst((h - PSF + 1) * PSTA);
            store_half<0>(acc0, o, h);
            if (L11 == h) ldfrag(11);
            if (L12 == h) { mbar_wait(bars + 8 * (B_XV + 2 + wg)); ldfrag(12); if (L13) ldfrag(13); }
        }
#pragma unroll
        for (int h = PK0; h < 14; h++) pack_half(acc0, h, pk + (h - PK0) * 4);
#pragma unroll
        for (int h = PK0; h < (ASP > CSP ? ASP : CSP); h++) { if (PSTA && wg == (ASP > CSP ? 0 : 1)) pst((h - PSF + 1) * PSTA); store_packed(o, h, pk + (h - PK0) * 4, ASP > CSP ? wg ^ 1 : wg); }
        TSF(3);
    }
    {
        if (L11 < 0) ldfrag(11);
        asm volatile("bar.sync %0, 256;" ::"r"(2 + wg) : "memory");
        TSF(4);
        const uint32_t b16 = launder();
#pragma unroll
        for (int st = 11; st < 16; st++) {
            wgmma_fence();
#pragma unroll
            for (int kk = 0; kk < 4; kk++) {
                const int i = (st - 11) * 4 + kk;
                wgmma_rs_n128(p0, af + i * 4, dB(b16, wofs(st, kk)));
                if (i == 0) TS9(1);
                constexpr int PD = L12 < 0 ? 1 : 2 + L13;
                if (kk == 0 && st + PD < 16) {
                    if (st == 11 && L12 < 0) mbar_wait(bars + 8 * (B_XV + 2 + wg));
                    if (st + PD == 14) mbar_wait(bars + 8 * (B_X15 + wg));
                    ldfrag(st + PD);
                }
                if (i % ISTEP == 0) {
                    const int h0 = ASP + i / ISTEP, h1 = CSP + i / ISTEP;
                    if (ASP == CSP) { if (h0 < 14) store_packed(o, h0, pk + (h0 - PK0) * 4, 1); }
                    else {
                        if (h0 < 14) store_packed(o, h0, pk + (h0 - PK0) * 4, wg ^ 1);
                        if (h1 < 14) store_packed(o, h1, pk + (h1 - PK0) * 4, wg);
                    }
                }
            }
        }
        wgmma_commit();
        asm volatile("bar.arrive %0, 256;" ::"r"(3 - wg) : "memory");
        TSF(5); TS9(2);
        if (PLAG && warp == 5) e_tma(bars + 8 * (B_L + 3), &tmx64, sbase + OFF_X + 2 * X_BYTES + 8192 + 16384, 10 * BK, mt * BM + 128 + 64);
        wgmma_wait<0>();
        TSF(6); TS9(3);
        if (PLAG && wg == 0) {
            if (w4 < 2) e_bulk_p(1, bars + 8 * B_L, W_BYTES / 2, sbase + OFF_X + w4 * X_BYTES, wgrp + (10 * 8 + w4 * 4) * BN);
            else if (w4 == 2) e_tma(bars + 8 * B_L, &tmx64, sbase + OFF_X + 2 * X_BYTES + 8192, 10 * BK, mt * BM + 64);
        }
        unsigned tb; asm volatile("mov.u32 %0, %%clock;" : "=r"(tb));
        auto pst = [&](unsigned t) { unsigned c; do { asm volatile("mov.u32 %0, %%clock;" : "=r"(c)); } while (c - tb < t); };
#pragma unroll
        for (int h = 0; h < (BSP > DSP ? BSP : DSP); h++) {
            if (h < BSP && h < DSP) { if (PSTB && wg == 0) pst(PSB0 + h * PSTB); if (PSTD && wg == 1) pst(h * PSTD); store_half<64 * F_>(p0, o, h); }
            else if (wg == (BSP > DSP ? 0 : 1)) { if (PSTB && wg == 0) pst(PSB0 + h * PSTB); store_half<64 * F_>(p0, o, h); }
        }
        TSF(7);
    }
    {
        if (PLAG == 1 || (PLAG == 3 && wg == 1)) { mbar_wait(bars + 8 * B_L); if (wg == 1) mbar_wait(bars + 8 * (B_L + 3)); }
        asm volatile("bar.sync %0, 256;" ::"r"(2 + wg) : "memory");
        TSF(8);
        const uint32_t b16 = launder();
        wgmma_fence();
#pragma unroll
        for (int i = 0; i < 20; i++) {
            wgmma_rs_n64(p1, af + i * 4, dB(b16, wofs(11 + (i >> 2), i & 3) + 128 * 16));
            if (i % ISTEP2 == 0) {
                const int h0 = BSP + i / ISTEP2, h1 = DSP + i / ISTEP2;
                if (BSP == DSP) { if (h0 < 8) store_half<64 * F_>(p0, o, h0); }
                else {
                    if (h0 < 8) store_half<64 * F_>(p0, o, h0, wg ^ 1);
                    if (h1 < 8) store_half<64 * F_>(p0, o, h1, wg);
                }
            }
        }
        if (PLAG) {
            if (PLAG == 2 || (PLAG == 3 && wg == 0)) { mbar_wait(bars + 8 * B_L); if (wg == 1) mbar_wait(bars + 8 * (B_L + 3)); }
#pragma unroll
            for (int kk = 0; kk < 4; kk++) wgmma_ss_n64(p1, dA(b16, xofs(11, kk, 1)), dB(b16, OFF_X + (kk >> 1) * X_BYTES + (kk & 1) * 2 * CHUNK_BYTES + 128 * 16));
        }
        wgmma_commit();
        if (PLAG) {
#pragma unroll
            for (int kk = 0; kk < 4; kk++) wgmma_ss_n32(p2, dA(b16, xofs(11, kk, 1)), dB(b16, OFF_X + (kk >> 1) * X_BYTES + (kk & 1) * 2 * CHUNK_BYTES + 192 * 16));
        }
#pragma unroll
        for (int i = 0; i < 20; i++) {
            wgmma_rs_n32(p2, af + i * 4, dB(b16, wofs(11 + (i >> 2), i & 3) + 192 * 16));
            if (i == NP2 - 1) {
                wgmma_commit();
                wgmma_wait<1>();
                TS9(4);
#pragma unroll
                for (int h = 0; h < 4; h++) store_half<64 * F_ + 128>(p1, o, h, NP2W == 2 ? 1 : wg);
                wgmma_fence();
            }
        }
        wgmma_commit();
        if (wg == 0) asm volatile("bar.arrive 3, 256;" ::: "memory");
        TSF(9);
        if (!NP2) { wgmma_wait<1>(); TS9(4); }
        if (!NP2 || (NP2W == 1 && wg == 0)) store_tile<64 * F_ + 128, 0, 2>(p1, o);
        wgmma_wait<0>();
        TSK(4, 63); TSF(10);
        store_tile<64 * F_ + 192, 0, 1>(p2, o);
        TSK(4, 77); TSF(11);
    }
}

typedef CUresult (*EncodeTiledFn)(CUtensorMap*, CUtensorMapDataType, cuuint32_t, void*, const cuuint64_t*, const cuuint64_t*, const cuuint32_t*, const cuuint32_t*, CUtensorMapInterleave, CUtensorMapSwizzle, CUtensorMapL2promotion, CUtensorMapFloatOOBfill);

extern "C" void kernel_launch(void* const* d_in, const int* in_sizes, int n_in, void* d_out, int out_size) {
    static EncodeTiledFn enc = nullptr;
    static decltype(&fused_kernel<true>) kern = nullptr;
    static void *p_w = nullptr, *p_flags = nullptr, *p_prof = nullptr;
    if (!enc) {
        void* fn = nullptr; cudaDriverEntryPointQueryResult qr;
        cudaGetDriverEntryPoint("cuTensorMapEncodeTiled", &fn, cudaEnableDefault, &qr);
        enc = (EncodeTiledFn)fn;
        int dev = 0, rsv = 0;
        cudaGetDevice(&dev);
        cudaDeviceGetAttribute(&rsv, cudaDevAttrReservedSharedMemoryPerBlock, dev);
        kern = HARDBASE && rsv == 1024 ? fused_kernel<true> : fused_kernel<false>;
        cudaFuncSetAttribute(kern, cudaFuncAttributeMaxDynamicSharedMemorySize, SMEM_BYTES);
        cudaGetSymbolAddress(&p_w, g_w);
        cudaGetSymbolAddress(&p_flags, g_flags);
    }
    CUtensorMap tmx, tmx64, tmq;
    {
        cuuint64_t gdim[2] = {(cuuint64_t)F_, (cuuint64_t)D_};
        cuuint64_t gstr[1] = {(cuuint64_t)F_ * 4};
        cuuint32_t box[2] = {(cuuint32_t)BN, 16};
        cuuint32_t estr[2] = {1, 1};
        enc(&tmq, CU_TENSOR_MAP_DATA_TYPE_INT32, 2, d_in[1], gdim, gstr, box, estr, CU_TENSOR_MAP_INTERLEAVE_NONE,
            CU_TENSOR_MAP_SWIZZLE_NONE, CU_TENSOR_MAP_L2_PROMOTION_L2_128B, CU_TENSOR_MAP_FLOAT_OOB_FILL_NONE);
    }
    {
        cuuint64_t gdim[2] = {(cuuint64_t)D_, (cuuint64_t)S_};
        cuuint64_t gstr[1] = {(cuuint64_t)D_ * 2};
        cuuint32_t box[2] = {(cuuint32_t)BK, (cuuint32_t)BM};
        cuuint32_t estr[2] = {1, 1};
        enc(&tmx, CU_TENSOR_MAP_DATA_TYPE_BFLOAT16, 2, d_in[0], gdim, gstr, box, estr, CU_TENSOR_MAP_INTERLEAVE_NONE,
            CU_TENSOR_MAP_SWIZZLE_128B, XPROMO, CU_TENSOR_MAP_FLOAT_OOB_FILL_NONE);
        box[1] = 64;
        enc(&tmx64, CU_TENSOR_MAP_DATA_TYPE_BFLOAT16, 2, d_in[0], gdim, gstr, box, estr, CU_TENSOR_MAP_INTERLEAVE_NONE,
            CU_TENSOR_MAP_SWIZZLE_128B, XPROMO, CU_TENSOR_MAP_FLOAT_OOB_FILL_NONE);
    }
    kern<<<128, 256, SMEM_BYTES>>>((const int*)d_in[1], (const unsigned short*)d_in[2], (__nv_bfloat16*)d_out, (uint4*)p_w, (unsigned*)p_flags, 0x80000000u, tmq, tmx64, tmx
    );
    (void)p_prof;
}
```

```cpp
#include <cuda_runtime.h>
#include <cuda_bf16.h>
#include <cuda.h>
#include <stdint.h>
#include <stdio.h>

#define LA 2
#define XPROMO CU_TENSOR_MAP_L2_PROMOTION_L2_128B
#define CSPLIT 5
#define FADDPOS 1
#define BSPLIT 4
#define DSPLIT 4
#define FLAGPOS 1
#define RAW1POS 5
#define PIPE 6
#define PR1 1100
#define LK 1
#define PX0 1150
#define PX1 100000
#define R2AT 0
#define R3AT 3
#define R4AT 4
#define W1EARLY 1
#define PR2 1700
#define PSTEP 0
#define PSBASE 0
#define NOW 2
#define R34AT 0
#define R1MODE 1
#define ST2 1
#define PR34 3500
#define DEADT 300
#define PPOLL 2800
#define ALLONLY 0
#define X1POST 0
#define W3FIRST 1
#define W1BY 3
#define W1D 150
#define F2POS 1
#define W2POS 0
#define W2D 200
#define W3D 0
#define W4L2 0
#define R3W1 4
#define VGRAN 32
#define X2POS 0
#define VSPLIT 0
#define NF 4
#define PAIR 0
#define ZPOS 10
#define PFX 0
#define PFXB 2
#define ASP 10
#define CSP 10
#define BSP 8
#define DSP 6
#define ISTEP 2
#define ISTEP2 2
#define PEEL 1
#define ILV 0
#define R4W0 0
#define PLAG 0
#define PSTA 110
#define PSF 2
#define PSTB 110
#define PSB0 200
#define L11 2
#define L12 7
#define L13 0
#define NP2 0
#define NP2W 1
#define PSTD 100
#define FASTINIT 0
#define R1PRE 0
#define L1PRE 1
#define XS 1
#define PX0B 2700
#define HARDBASE 1

constexpr int S_ = 2048, D_ = 1024, F_ = 3584;
constexpr int BM = 256, BN = 224, BK = 64;
constexpr int X_BYTES = BM * BK * 2;
constexpr int W_BYTES = BN * BK * 2;
constexpr int CHUNK_BYTES = BN * 16;
constexpr int OFF_X = 0;
constexpr int OFF_W = 3 * X_BYTES;
constexpr int OFF_STG = OFF_W + 3 * W_BYTES;
constexpr int OFF_LUT = OFF_W + 4 * W_BYTES;
constexpr int OFF_BAR = OFF_LUT + 7 * 2048;
constexpr int OFF_PROF = OFF_BAR + 1024;
constexpr int SMEM_BYTES = OFF_PROF + 1024 + 1024;
constexpr int B_FULL = 0;
constexpr int B_XV = 12;
constexpr int B_WF = 17;
constexpr int B_EMPTY = 22;
constexpr int B_DQ = 34;
constexpr int B_SLAB = 42;
constexpr int B_L = 34;
constexpr int B_X15 = 35;
constexpr int B_LUT = 46;

__device__ __align__(1024) uint4 g_w[(size_t)F_ * D_ / 8];
__device__ __align__(128) unsigned g_flags[16 * 32];

__device__ __forceinline__ uint32_t smem_u32(const void* p) { return (uint32_t)__cvta_generic_to_shared(p); }
__device__ __forceinline__ void mbar_init(uint32_t bar, uint32_t cnt) { asm volatile("mbarrier.init.shared::cta.b64 [%0], %1;" ::"r"(bar), "r"(cnt) : "memory"); }
__device__ __forceinline__ void mbar_wait(uint32_t bar) {
    asm volatile("{\n.reg .pred p;\nWAIT_LOOP:\nmbarrier.try_wait.parity.shared::cta.b64 p, [%0], 0;\n@p bra WAIT_DONE;\nbra WAIT_LOOP;\nWAIT_DONE:\n}" ::"r"(bar) : "memory");
}
__device__ __forceinline__ void e_arrive(uint32_t bar) {
    asm volatile("{\n.reg .pred p;\nelect.sync _|p, 0xffffffff;\n@p mbarrier.arrive.shared::cta.b64 _, [%0];\n}" ::"r"(bar) : "memory");
}
__device__ __forceinline__ void e_expect(uint32_t bar, uint32_t bytes) {
    asm volatile("{\n.reg .pred p;\nelect.sync _|p, 0xffffffff;\n@p mbarrier.arrive.expect_tx.shared::cta.b64 _, [%0], %1;\n}" ::"r"(bar), "r"(bytes) : "memory");
}
__device__ __forceinline__ void e_tma(uint32_t bar, const CUtensorMap* tm, uint32_t d0, int x0, int y0) {
    asm volatile("{\n.reg .pred p;\nelect.sync _|p, 0xffffffff;\n"
                 "@p cp.async.bulk.tensor.2d.shared::cluster.global.mbarrier::complete_tx::bytes [%2], [%1, {%3, %4}], [%0];\n}"
                 ::"r"(bar), "l"(tm), "r"(d0), "r"(x0), "r"(y0) : "memory");
}
__device__ __forceinline__ void e_bulk(uint32_t bar, uint32_t bytes, uint32_t dst, const void* src) {
    asm volatile("{\n.reg .pred p;\nelect.sync _|p, 0xffffffff;\n"
                 "@p mbarrier.arrive.expect_tx.shared::cta.b64 _, [%0], %1;\n"
                 "@p cp.async.bulk.shared::cluster.global.mbarrier::complete_tx::bytes [%2], [%3], %1, [%0];\n}"
                 ::"r"(bar), "r"(bytes), "r"(dst), "l"(src) : "memory");
}
__device__ __forceinline__ void e_bulk_p(uint32_t on, uint32_t bar, uint32_t bytes, uint32_t dst, const void* src) {
    if (on) asm volatile("{\n.reg .pred p;\nelect.sync _|p, 0xffffffff;\n"
                         "@p cp.async.bulk.shared::cluster.global.mbarrier::complete_tx::bytes [%2], [%3], %1, [%0];\n}"
                         ::"r"(bar), "r"(bytes), "r"(dst), "l"(src) : "memory");
}
__device__ __forceinline__ void e_prefetch2d(const CUtensorMap* tm, int x, int y) {
    asm volatile("{\n.reg .pred p;\nelect.sync _|p, 0xffffffff;\n@p cp.async.bulk.prefetch.tensor.2d.L2.global [%0, {%1, %2}];\n}" ::"l"(tm), "r"(x), "r"(y) : "memory");
}
#define FASTREL 0
__device__ __forceinline__ void e_publish(unsigned* flag) {
    asm volatile("{\n.reg .pred p;\nelect.sync _|p, 0xffffffff;\n@p red.release.gpu.global.add.u32 [%0], 1;\n}" ::"l"(flag) : "memory");
}
__device__ __forceinline__ void e_red(unsigned* flag, unsigned v) {
    asm volatile("{\n.reg .pred p;\nelect.sync _|p, 0xffffffff;\n@p red.relaxed.gpu.global.add.u32 [%0], %1;\n}" ::"l"(flag), "r"(v) : "memory");
}
__device__ __forceinline__ bool mbar_test(uint32_t bar) {
    uint32_t r;
    asm volatile("{\n.reg .pred p;\nmbarrier.test_wait.parity.shared::cta.b64 p, [%1], 0;\nselp.u32 %0, 1, 0, p;\n}" : "=r"(r) : "r"(bar) : "memory");
    return __all_sync(0xffffffff, r != 0);
}
template <int V> struct IC { static constexpr int value = V; };
__device__ __forceinline__ unsigned ld_flag(const unsigned* f) { unsigned v; asm volatile("ld.relaxed.gpu.global.u32 %0, [%1];" : "=r"(v) : "l"(f) : "memory"); return v; }
__device__ __forceinline__ void finish_poll(const unsigned* f, unsigned v, unsigned target) {
    int n = 0;
    while (!__all_sync(0xffffffff, (int)(v - target) >= 0) && ++n < 4000000) v = ld_flag(f);
    asm volatile("fence.acquire.gpu;" ::: "memory");
    asm volatile("fence.proxy.async.global;" ::: "memory");
}
template <typename T> __device__ __forceinline__ T* ptr_add(T* base, uint32_t off) {
    uint64_t r;
    asm("{\n.reg .u32 l, h;\nmov.b64 {l, h}, %1;\nadd.cc.u32 l, l, %2;\naddc.u32 h, h, 0;\nmov.b64 %0, {l, h};\n}" : "=l"(r) : "l"(base), "r"(off));
    return (T*)r;
}
__device__ __forceinline__ void wgmma_fence() { asm volatile("wgmma.fence.sync.aligned;" ::: "memory"); }
__device__ __forceinline__ void wgmma_commit() { asm volatile("wgmma.commit_group.sync.aligned;" ::: "memory"); }
template <int N> __device__ __forceinline__ void wgmma_wait() { asm volatile("wgmma.wait_group.sync.aligned %0;" ::"n"(N) : "memory"); }
__device__ __forceinline__ void wgmma_m64n224k16(float (&d)[112], uint64_t da, uint64_t db, int scale_d) {
    asm volatile(
        "{\n.reg .pred p;\nsetp.ne.b32 p, %114, 0;\n"
        "wgmma.mma_async.sync.aligned.m64n224k16.f32.bf16.bf16 "
        "{%0, %1, %2, %3, %4, %5, %6, %7, %8, %9, %10, %11, %12, %13, %14, %15, "
        "%16, %17, %18, %19, %20, %21, %22, %23, %24, %25, %26, %27, %28, %29, %30, %31, "
        "%32, %33, %34, %35, %36, %37, %38, %39, %40, %41, %42, %43, %44, %45, %46, %47, "
        "%48, %49, %50, %51, %52, %53, %54, %55, %56, %57, %58, %59, %60, %61, %62, %63, "
        "%64, %65, %66, %67, %68, %69, %70, %71, %72, %73, %74, %75, %76, %77, %78, %79, "
        "%80, %81, %82, %83, %84, %85, %86, %87, %88, %89, %90, %91, %92, %93, %94, %95, "
        "%96, %97, %98, %99, %100, %101, %102, %103, %104, %105, %106, %107, %108, %109, %110, %111}, "
        "%112, %113, p, 1, 1, 0, 0;\n}\n"
        : "+f"(d[0]), "+f"(d[1]), "+f"(d[2]), "+f"(d[3]), "+f"(d[4]), "+f"(d[5]), "+f"(d[6]), "+f"(d[7]),
          "+f"(d[8]), "+f"(d[9]), "+f"(d[10]), "+f"(d[11]), "+f"(d[12]), "+f"(d[13]), "+f"(d[14]), "+f"(d[15]),
          "+f"(d[16]), "+f"(d[17]), "+f"(d[18]), "+f"(d[19]), "+f"(d[20]), "+f"(d[21]), "+f"(d[22]), "+f"(d[23]),
          "+f"(d[24]), "+f"(d[25]), "+f"(d[26]), "+f"(d[27]), "+f"(d[28]), "+f"(d[29]), "+f"(d[30]), "+f"(d[31]),
          "+f"(d[32]), "+f"(d[33]), "+f"(d[34]), "+f"(d[35]), "+f"(d[36]), "+f"(d[37]), "+f"(d[38]), "+f"(d[39]),
          "+f"(d[40]), "+f"(d[41]), "+f"(d[42]), "+f"(d[43]), "+f"(d[44]), "+f"(d[45]), "+f"(d[46]), "+f"(d[47]),
          "+f"(d[48]), "+f"(d[49]), "+f"(d[50]), "+f"(d[51]), "+f"(d[52]), "+f"(d[53]), "+f"(d[54]), "+f"(d[55]),
          "+f"(d[56]), "+f"(d[57]), "+f"(d[58]), "+f"(d[59]), "+f"(d[60]), "+f"(d[61]), "+f"(d[62]), "+f"(d[63]),
          "+f"(d[64]), "+f"(d[65]), "+f"(d[66]), "+f"(d[67]), "+f"(d[68]), "+f"(d[69]), "+f"(d[70]), "+f"(d[71]),
          "+f"(d[72]), "+f"(d[73]), "+f"(d[74]), "+f"(d[75]), "+f"(d[76]), "+f"(d[77]), "+f"(d[78]), "+f"(d[79]),
          "+f"(d[80]), "+f"(d[81]), "+f"(d[82]), "+f"(d[83]), "+f"(d[84]), "+f"(d[85]), "+f"(d[86]), "+f"(d[87]),
          "+f"(d[88]), "+f"(d[89]), "+f"(d[90]), "+f"(d[91]), "+f"(d[92]), "+f"(d[93]), "+f"(d[94]), "+f"(d[95]),
          "+f"(d[96]), "+f"(d[97]), "+f"(d[98]), "+f"(d[99]), "+f"(d[100]), "+f"(d[101]), "+f"(d[102]), "+f"(d[103]),
          "+f"(d[104]), "+f"(d[105]), "+f"(d[106]), "+f"(d[107]), "+f"(d[108]), "+f"(d[109]), "+f"(d[110]), "+f"(d[111])
        : "l"(da), "l"(db), "r"(scale_d));
}

__device__ __forceinline__ void wgmma_rs_n32(float (&d)[16], const uint32_t* a, uint64_t db) {
    asm volatile("wgmma.mma_async.sync.aligned.m64n32k16.f32.bf16.bf16 {%0, %1, %2, %3, %4, %5, %6, %7, %8, %9, %10, %11, %12, %13, %14, %15}, {%16, %17, %18, %19}, %20, 1, 1, 1, 0;"
        : "+f"(d[0]), "+f"(d[1]), "+f"(d[2]), "+f"(d[3]), "+f"(d[4]), "+f"(d[5]), "+f"(d[6]), "+f"(d[7]), "+f"(d[8]), "+f"(d[9]), "+f"(d[10]), "+f"(d[11]), "+f"(d[12]), "+f"(d[13]), "+f"(d[14]), "+f"(d[15])
        : "r"(a[0]), "r"(a[1]), "r"(a[2]), "r"(a[3]), "l"(db));
}
__device__ __forceinline__ void wgmma_ss_n32(float (&d)[16], uint64_t da, uint64_t db) {
    asm volatile("wgmma.mma_async.sync.aligned.m64n32k16.f32.bf16.bf16 {%0, %1, %2, %3, %4, %5, %6, %7, %8, %9, %10, %11, %12, %13, %14, %15}, %16, %17, 1, 1, 1, 0, 0;"
        : "+f"(d[0]), "+f"(d[1]), "+f"(d[2]), "+f"(d[3]), "+f"(d[4]), "+f"(d[5]), "+f"(d[6]), "+f"(d[7]), "+f"(d[8]), "+f"(d[9]), "+f"(d[10]), "+f"(d[11]), "+f"(d[12]), "+f"(d[13]), "+f"(d[14]), "+f"(d[15])
        : "l"(da), "l"(db));
}
__device__ __forceinline__ void wgmma_rs_n64(float (&d)[32], const uint32_t* a, uint64_t db) {
    asm volatile("wgmma.mma_async.sync.aligned.m64n64k16.f32.bf16.bf16 {%0, %1, %2, %3, %4, %5, %6, %7, %8, %9, %10, %11, %12, %13, %14, %15, %16, %17, %18, %19, %20, %21, %22, %23, %24, %25, %26, %27, %28, %29, %30, %31}, {%32, %33, %34, %35}, %36, 1, 1, 1, 0;"
        : "+f"(d[0]), "+f"(d[1]), "+f"(d[2]), "+f"(d[3]), "+f"(d[4]), "+f"(d[5]), "+f"(d[6]), "+f"(d[7]), "+f"(d[8]), "+f"(d[9]), "+f"(d[10]), "+f"(d[11]), "+f"(d[12]), "+f"(d[13]), "+f"(d[14]), "+f"(d[15]), "+f"(d[16]), "+f"(d[17]), "+f"(d[18]), "+f"(d[19]), "+f"(d[20]), "+f"(d[21]), "+f"(d[22]), "+f"(d[23]), "+f"(d[24]), "+f"(d[25]), "+f"(d[26]), "+f"(d[27]), "+f"(d[28]), "+f"(d[29]), "+f"(d[30]), "+f"(d[31])
        : "r"(a[0]), "r"(a[1]), "r"(a[2]), "r"(a[3]), "l"(db));
}
__device__ __forceinline__ void wgmma_ss_n64(float (&d)[32], uint64_t da, uint64_t db) {
    asm volatile("wgmma.mma_async.sync.aligned.m64n64k16.f32.bf16.bf16 {%0, %1, %2, %3, %4, %5, %6, %7, %8, %9, %10, %11, %12, %13, %14, %15, %16, %17, %18, %19, %20, %21, %22, %23, %24, %25, %26, %27, %28, %29, %30, %31}, %32, %33, 1, 1, 1, 0, 0;"
        : "+f"(d[0]), "+f"(d[1]), "+f"(d[2]), "+f"(d[3]), "+f"(d[4]), "+f"(d[5]), "+f"(d[6]), "+f"(d[7]), "+f"(d[8]), "+f"(d[9]), "+f"(d[10]), "+f"(d[11]), "+f"(d[12]), "+f"(d[13]), "+f"(d[14]), "+f"(d[15]), "+f"(d[16]), "+f"(d[17]), "+f"(d[18]), "+f"(d[19]), "+f"(d[20]), "+f"(d[21]), "+f"(d[22]), "+f"(d[23]), "+f"(d[24]), "+f"(d[25]), "+f"(d[26]), "+f"(d[27]), "+f"(d[28]), "+f"(d[29]), "+f"(d[30]), "+f"(d[31])
        : "l"(da), "l"(db));
}
__device__ __forceinline__ void wgmma_rs_n128(float (&d)[64], const uint32_t* a, uint64_t db) {
    asm volatile("wgmma.mma_async.sync.aligned.m64n128k16.f32.bf16.bf16 {%0, %1, %2, %3, %4, %5, %6, %7, %8, %9, %10, %11, %12, %13, %14, %15, %16, %17, %18, %19, %20, %21, %22, %23, %24, %25, %26, %27, %28, %29, %30, %31, %32, %33, %34, %35, %36, %37, %38, %39, %40, %41, %42, %43, %44, %45, %46, %47, %48, %49, %50, %51, %52, %53, %54, %55, %56, %57, %58, %59, %60, %61, %62, %63}, {%64, %65, %66, %67}, %68, 1, 1, 1, 0;"
        : "+f"(d[0]), "+f"(d[1]), "+f"(d[2]), "+f"(d[3]), "+f"(d[4]), "+f"(d[5]), "+f"(d[6]), "+f"(d[7]), "+f"(d[8]), "+f"(d[9]), "+f"(d[10]), "+f"(d[11]), "+f"(d[12]), "+f"(d[13]), "+f"(d[14]), "+f"(d[15]), "+f"(d[16]), "+f"(d[17]), "+f"(d[18]), "+f"(d[19]), "+f"(d[20]), "+f"(d[21]), "+f"(d[22]), "+f"(d[23]), "+f"(d[24]), "+f"(d[25]), "+f"(d[26]), "+f"(d[27]), "+f"(d[28]), "+f"(d[29]), "+f"(d[30]), "+f"(d[31]), "+f"(d[32]), "+f"(d[33]), "+f"(d[34]), "+f"(d[35]), "+f"(d[36]), "+f"(d[37]), "+f"(d[38]), "+f"(d[39]), "+f"(d[40]), "+f"(d[41]), "+f"(d[42]), "+f"(d[43]), "+f"(d[44]), "+f"(d[45]), "+f"(d[46]), "+f"(d[47]), "+f"(d[48]), "+f"(d[49]), "+f"(d[50]), "+f"(d[51]), "+f"(d[52]), "+f"(d[53]), "+f"(d[54]), "+f"(d[55]), "+f"(d[56]), "+f"(d[57]), "+f"(d[58]), "+f"(d[59]), "+f"(d[60]), "+f"(d[61]), "+f"(d[62]), "+f"(d[63])
        : "r"(a[0]), "r"(a[1]), "r"(a[2]), "r"(a[3]), "l"(db));
}
__device__ __forceinline__ void wgmma_ss_n128(float (&d)[64], uint64_t da, uint64_t db) {
    asm volatile("wgmma.mma_async.sync.aligned.m64n128k16.f32.bf16.bf16 {%0, %1, %2, %3, %4, %5, %6, %7, %8, %9, %10, %11, %12, %13, %14, %15, %16, %17, %18, %19, %20, %21, %22, %23, %24, %25, %26, %27, %28, %29, %30, %31, %32, %33, %34, %35, %36, %37, %38, %39, %40, %41, %42, %43, %44, %45, %46, %47, %48, %49, %50, %51, %52, %53, %54, %55, %56, %57, %58, %59, %60, %61, %62, %63}, %64, %65, 1, 1, 1, 0, 0;"
        : "+f"(d[0]), "+f"(d[1]), "+f"(d[2]), "+f"(d[3]), "+f"(d[4]), "+f"(d[5]), "+f"(d[6]), "+f"(d[7]), "+f"(d[8]), "+f"(d[9]), "+f"(d[10]), "+f"(d[11]), "+f"(d[12]), "+f"(d[13]), "+f"(d[14]), "+f"(d[15]), "+f"(d[16]), "+f"(d[17]), "+f"(d[18]), "+f"(d[19]), "+f"(d[20]), "+f"(d[21]), "+f"(d[22]), "+f"(d[23]), "+f"(d[24]), "+f"(d[25]), "+f"(d[26]), "+f"(d[27]), "+f"(d[28]), "+f"(d[29]), "+f"(d[30]), "+f"(d[31]), "+f"(d[32]), "+f"(d[33]), "+f"(d[34]), "+f"(d[35]), "+f"(d[36]), "+f"(d[37]), "+f"(d[38]), "+f"(d[39]), "+f"(d[40]), "+f"(d[41]), "+f"(d[42]), "+f"(d[43]), "+f"(d[44]), "+f"(d[45]), "+f"(d[46]), "+f"(d[47]), "+f"(d[48]), "+f"(d[49]), "+f"(d[50]), "+f"(d[51]), "+f"(d[52]), "+f"(d[53]), "+f"(d[54]), "+f"(d[55]), "+f"(d[56]), "+f"(d[57]), "+f"(d[58]), "+f"(d[59]), "+f"(d[60]), "+f"(d[61]), "+f"(d[62]), "+f"(d[63])
        : "l"(da), "l"(db));
}

__device__ __forceinline__ uint32_t pack_bf16(float lo, float hi) {
    uint32_t r; asm("cvt.rn.bf16x2.f32 %0, %1, %2;" : "=r"(r) : "f"(hi), "f"(lo)); return r;
}
__device__ __forceinline__ uint32_t lds32(uint32_t a) { uint32_t v; asm volatile("ld.shared.b32 %0, [%1];" : "=r"(v) : "r"(a)); return v; }
__device__ __forceinline__ void sts32(uint32_t a, uint32_t v) { asm volatile("st.shared.b32 [%0], %1;" ::"r"(a), "r"(v) : "memory"); }
__device__ __forceinline__ void sts128(uint32_t a, uint4 v) { asm volatile("st.shared.v4.b32 [%0], {%1,%2,%3,%4};" ::"r"(a), "r"(v.x), "r"(v.y), "r"(v.z), "r"(v.w) : "memory"); }
__device__ __forceinline__ void stg128(void* p, uint4 v) { asm volatile("st.global.v4.b32 [%0], {%1,%2,%3,%4};" ::"l"(p), "r"(v.x), "r"(v.y), "r"(v.z), "r"(v.w) : "memory"); }
__device__ __forceinline__ void cp16(uint32_t dst, const void* src) { asm volatile("cp.async.cg.shared.global [%0], [%1], 16;" ::"r"(dst), "l"(src) : "memory"); }
__device__ __forceinline__ void cp_commit() { asm volatile("cp.async.commit_group;" ::: "memory"); }
template <int N> __device__ __forceinline__ void cp_wait() { asm volatile("cp.async.wait_group %0;" ::"n"(N) : "memory"); }
__device__ __forceinline__ uint4 dequant8(uint32_t raw, uint32_t lut_a) {
    uint32_t v[8];
#pragma unroll
    for (int i = 0; i < 8; i++) v[i] = lds32(raw + i * 128);
#pragma unroll
    for (int i = 0; i < 8; i++) v[i] = lds32(lut_a + v[i] * 128);
    uint4 o;
    o.x = __byte_perm(v[0], v[1], 0x5410); o.y = __byte_perm(v[2], v[3], 0x5410);
    o.z = __byte_perm(v[4], v[5], 0x5410); o.w = __byte_perm(v[6], v[7], 0x5410);
    return o;
}
__device__ __forceinline__ uint32_t prmt(uint32_t a, uint32_t b, uint32_t c) { uint32_t r; asm("prmt.b32 %0, %1, %2, %3;" : "=r"(r) : "r"(a), "r"(b), "r"(c)); return r; }
__device__ __forceinline__ uint4 lookup8_reg(const uint32_t* c, const uint32_t (&T)[8], uint32_t two31) {
    uint32_t o[4];
#pragma unroll
    for (int h = 0; h < 2; h++) {
        const uint32_t sel = c[4 * h] + c[4 * h + 1] * 16 + c[4 * h + 2] * 256 + c[4 * h + 3] * 4096;
        const uint32_t s7 = sel & 0x7777u;
        uint32_t m;
        asm("lop3.b32 %0, %1, %2, 0x3210, 0xEA;" : "=r"(m) : "r"(__umulhi(sel, two31)), "r"(0x4444u));
        const uint32_t lo = prmt(prmt(T[0], T[1], s7), prmt(T[2], T[3], s7), m);
        const uint32_t hi = prmt(prmt(T[4], T[5], s7), prmt(T[6], T[7], s7), m);
        o[2 * h] = prmt(lo, hi, 0x5140u); o[2 * h + 1] = prmt(lo, hi, 0x7362u);
    }
    return make_uint4(o[0], o[1], o[2], o[3]);
}
template <int OFF, int G0, int G1, int N>
__device__ __forceinline__ void store_tile(const float (&acc)[N], __nv_bfloat16* o) {
#pragma unroll
    for (int G = G0; G < G1; G++) {
        uint4 v;
        v.x = pack_bf16(acc[G * 16 + 0], acc[G * 16 + 1]); v.y = pack_bf16(acc[G * 16 + 4], acc[G * 16 + 5]);
        v.z = pack_bf16(acc[G * 16 + 8], acc[G * 16 + 9]); v.w = pack_bf16(acc[G * 16 + 12], acc[G * 16 + 13]);
        stg128(o + OFF + G * 32, v);
        v.x = pack_bf16(acc[G * 16 + 2], acc[G * 16 + 3]); v.y = pack_bf16(acc[G * 16 + 6], acc[G * 16 + 7]);
        v.z = pack_bf16(acc[G * 16 + 10], acc[G * 16 + 11]); v.w = pack_bf16(acc[G * 16 + 14], acc[G * 16 + 15]);
        stg128(o + OFF + 8 * F_ + G * 32, v);
    }
}
template <int OFF, int N>
__device__ __forceinline__ void store_half(const float (&acc)[N], __nv_bfloat16* o, int H, int on = 1) {
    const int b = (H >> 1) * 16 + (H & 1) * 2;
    uint4 v;
    v.x = pack_bf16(acc[b + 0], acc[b + 1]); v.y = pack_bf16(acc[b + 4], acc[b + 5]);
    v.z = pack_bf16(acc[b + 8], acc[b + 9]); v.w = pack_bf16(acc[b + 12], acc[b + 13]);
    asm volatile("{\n.reg .pred p;\nsetp.ne.b32 p, %5, 0;\n@p st.global.v4.b32 [%0], {%1,%2,%3,%4};\n}"
                 ::"l"(o + OFF + (H & 1) * 8 * F_ + (H >> 1) * 32), "r"(v.x), "r"(v.y), "r"(v.z), "r"(v.w), "r"(on) : "memory");
}
template <int N>
__device__ __forceinline__ void pack_half(const float (&acc)[N], int H, uint32_t* r) {
    const int b = (H >> 1) * 16 + (H & 1) * 2;
#pragma unroll
    for (int i = 0; i < 4; i++) asm volatile("cvt.rn.bf16x2.f32 %0, %1, %2;" : "=r"(r[i]) : "f"(acc[b + 4 * i + 1]), "f"(acc[b + 4 * i]));
}
__device__ __forceinline__ void store_packed(__nv_bfloat16* o, int H, const uint32_t* r, int on) {
    asm volatile("{\n.reg .pred p;\nsetp.ne.b32 p, %5, 0;\n@p st.global.v4.b32 [%0], {%1,%2,%3,%4};\n}"
                 ::"l"(o + (H & 1) * 8 * F_ + (H >> 1) * 32), "r"(r[0]), "r"(r[1]), "r"(r[2]), "r"(r[3]), "r"(on) : "memory");
}
constexpr int NROUNDS = 8;
constexpr unsigned long long R_FIRST = 0xFDB97543ull, R_BATCH = 0x60050400ull, R_DOUBLE = 0x7C;
constexpr unsigned long long W_FLAG = 0x600504000ull;
constexpr unsigned L1_MASK = W4L2 ? 0x2A : 0x2E, L2_MASK = W4L2 ? 0x1EA : 0x1E8; constexpr int W12_AT = 8;
constexpr int NFAST = NF;
__device__ __forceinline__ int round_first(int r) { return (int)(R_FIRST >> (4 * r)) & 15; }
__device__ __forceinline__ int round_batch(int r) { return (int)(R_BATCH >> (4 * r)) & 15; }

#define TSK(w, i)
#define TSF(i)
#define TSP(i)
#define TSQ(i)
#define PW 0
#define TS9(i)
#define TS8(i)
#define TSW(w, i)

template <bool HARD>
__global__ void __launch_bounds__(256, 1)
fused_kernel(const int* __restrict__ qw, const unsigned short* __restrict__ lut, __nv_bfloat16* __restrict__ out,
             uint4* __restrict__ wscr, unsigned* __restrict__ flags, const uint32_t two31,
             const __grid_constant__ CUtensorMap tmq, const __grid_constant__ CUtensorMap tmx64, const __grid_constant__ CUtensorMap tmx
) {
    extern __shared__ uint8_t smem_raw[];
    const uint32_t sbase = HARD ? 1024u : (smem_u32(smem_raw) + 1023) & ~1023u;
    const uint32_t bars = sbase + OFF_BAR;
    const int tid = threadIdx.x, lane = tid & 31;
    const int mt = blockIdx.x & 7, g = blockIdx.x >> 3;
    unsigned clk0; asm volatile("mov.u32 %0, %%clock;" : "=r"(clk0));
    constexpr int SLAB_BYTES = 16 * BN * 4, OFF_SLAB0 = OFF_W + 2 * W_BYTES, OFF_SLAB2 = OFF_X + 2 * X_BYTES;
    const int warp = __shfl_sync(0xffffffff, tid >> 5, 0);
    if (tid >= 224) {
        asm volatile("{\n.reg .pred p;\nelect.sync _|p, 0xffffffff;\n"
                     "@p mbarrier.init.shared::cta.b64 [%0], 1;\n"
                     "@p fence.mbarrier_init.release.cluster;\n"
                     "@p mbarrier.arrive.expect_tx.shared::cta.b64 _, [%0], %1;\n"
                     "@p cp.async.bulk.tensor.2d.shared::cluster.global.mbarrier::complete_tx::bytes [%3], [%2, {%4, 0}], [%0];\n}"
                     ::"r"(bars + 8 * B_SLAB), "n"(SLAB_BYTES), "l"(&tmq), "r"(sbase + OFF_SLAB0), "r"(g * BN) : "memory");
    } else {
        const unsigned short* lp = ptr_add(lut, ((lane >> 2) * F_ + g * BN + (tid & ~31) + (lane & 3) * 8) * 2);
        asm volatile("cp.async.cg.shared.global [%0], [%1], 16;\ncp.async.cg.shared.global [%0+512], [%1+57344], 16;\ncp.async.commit_group;"
                     ::"r"(sbase + OFF_STG + (tid >> 5) * 4096 + lane * 16), "l"(lp) : "memory");
    }
    const int sl = warp - 3;
    auto load_slab = [&]() {
        e_tma(bars + 8 * (B_SLAB + sl), &tmq, sbase + (sl < 2 ? OFF_SLAB0 : OFF_SLAB2 - 2 * SLAB_BYTES) + sl * SLAB_BYTES, g * BN, sl * 16);
    };
    if (warp >= 4 && warp < 7) {
        asm volatile("{\n.reg .pred p;\nelect.sync _|p, 0xffffffff;\n"
                     "@p mbarrier.init.shared::cta.b64 [%0], 1;\n"
                     "@p fence.mbarrier_init.release.cluster;\n"
                     "@p mbarrier.arrive.expect_tx.shared::cta.b64 _, [%0], %1;\n}"
                     ::"r"(bars + 8 * (B_SLAB + sl)), "n"(SLAB_BYTES) : "memory");
        if (sl < NOW) load_slab();
    } else if (warp < 2) {
        asm volatile("{\n.reg .pred p;\nelect.sync _|p, 0xffffffff;\n"
                     "@p mbarrier.init.shared::cta.b64 [%0], %1;\n"
                     "@p fence.mbarrier_init.release.cluster;\n}" ::"r"(bars + 8 * (warp ? B_LUT : B_FULL)), "r"(8 - warp) : "memory");
    }
    asm volatile("bar.sync 1, 256;" ::: "memory");
    TSQ(0);
    const int wg = warp >> 2;

    const int fl = 8 * ((lane & 7) >> 1) + 2 * (lane >> 3) + (lane & 1);
    const uint32_t lut_a = sbase + OFF_LUT + warp * 2048 + lane * 4;
    const uint32_t stg = sbase + OFF_STG + warp * 4096;
    unsigned* myflags = flags + g * 32;
    const uint4* wgrp = wscr + (size_t)g * 128 * BN;
    unsigned target = 0;

    auto issue_x = [&](int s, int slot) {
        e_tma(bars + 8 * (B_FULL + s), &tmx, sbase + OFF_X + slot * X_BYTES, s * BK, mt * BM);
    };
    auto pf_x = [&](int s, int row0) { e_prefetch2d(&tmx64, s * BK, row0); };
    auto issue_xv = [&](int v, int w, uint32_t bar) {
        const uint32_t dst = sbase + OFF_X + (v & 1) * X_BYTES + w * 16384;
        const int k0 = (12 + 2 * (v & 1)) * BK, r0 = mt * BM + w * 128 + ((v >> 1) & 1) * 64;
        e_tma(bar, &tmx64, dst, k0, r0);
        e_tma(bar, &tmx64, dst + 8192, k0 + BK, r0);
    };
    auto issue_w = [&](int s, int slot, int bar) {
        e_bulk(bars + 8 * bar, W_BYTES, sbase + OFF_W + slot * W_BYTES, wgrp + s * 8 * BN);
    };
    auto load_raw = [&](int t) {
        if (t < 16) {
            const int* src = ptr_add(qw, (uint32_t)(((t * BK + mt * 8 + (lane >> 3)) * F_ + g * BN + warp * 32 + (lane & 7) * 4) * 4));
            asm volatile("cp.async.cg.shared.global [%0], [%1], 16;\ncp.async.cg.shared.global [%0+512], [%1+57344], 16;"
                         ::"r"(stg + (t & 3) * 1024 + lane * 16), "l"(src) : "memory");
        }
        cp_commit();
    };
    auto load_blk = [&](int t, int c) {
        const int* src = ptr_add(qw, (uint32_t)(((t * BK + mt * 8 + (lane >> 3)) * F_ + g * BN + c * 32 + (lane & 7) * 4) * 4));
        asm volatile("cp.async.cg.shared.global [%0], [%1], 16;\ncp.async.cg.shared.global [%0+512], [%1+57344], 16;"
                     ::"r"(sbase + OFF_STG + c * 4096 + t * 1024 + lane * 16), "l"(src) : "memory");
    };
    auto foreign = [&](int t) {
        const int c = warp ^ 4;
        stg128(ptr_add(wscr, (uint32_t)(((g * 128 + t * 8 + mt) * BN + c * 32 + lane) * 16)),
               dequant8(sbase + OFF_STG + c * 4096 + t * 1024 + fl * 4, sbase + OFF_LUT + c * 2048 + lane * 4));
        TSW(4, 5);
    };
    auto my_unit = [&](int t) { return ptr_add(wscr, (uint32_t)(((g * 128 + t * 8 + mt) * BN + warp * 32 + lane) * 16)); };
    auto coop = [&](int t) {
        cp_wait<LA - 1>();
        __syncwarp();
        load_raw(t + LA);
        stg128(my_unit(t), dequant8(stg + (t & 3) * 1024 + fl * 4, lut_a));

    };
    auto coop2 = [&](int t) {
        cp_wait<0>();
        __syncwarp();
        if (t < 14) {
            const int* src = ptr_add(qw, (uint32_t)((((t + 2) * BK + mt * 8 + (lane >> 3)) * F_ + g * BN + warp * 32 + (lane & 7) * 4) * 4));
            asm volatile("cp.async.cg.shared.global [%0], [%1], 16;\ncp.async.cg.shared.global [%0+512], [%1+57344], 16;"
                         ::"r"(stg + ((t + 2) & 3) * 1024 + lane * 16), "l"(src) : "memory");
            if (t < 13) asm volatile("cp.async.cg.shared.global [%0], [%1+917504], 16;\ncp.async.cg.shared.global [%0+512], [%1+974848], 16;"
                                     ::"r"(stg + ((t + 3) & 3) * 1024 + lane * 16), "l"(src) : "memory");
            cp_commit();
        }
        uint32_t v[16];
        const uint32_t r0 = stg + (t & 3) * 1024 + fl * 4, r1 = stg + ((t + 1) & 3) * 1024 + fl * 4;
#pragma unroll
        for (int i = 0; i < 8; i++) v[i] = lds32(r0 + i * 128);
#pragma unroll
        for (int i = 0; i < 8; i++) v[8 + i] = lds32(r1 + i * 128);
#pragma unroll
        for (int i = 0; i < 16; i++) v[i] = lds32(lut_a + v[i] * 128);
        uint4* dst = my_unit(t);
        stg128(dst, make_uint4(prmt(v[0], v[1], 0x5410), prmt(v[2], v[3], 0x5410), prmt(v[4], v[5], 0x5410), prmt(v[6], v[7], 0x5410)));
        if (t < 15) stg128(dst + 8 * BN, make_uint4(prmt(v[8], v[9], 0x5410), prmt(v[10], v[11], 0x5410), prmt(v[12], v[13], 0x5410), prmt(v[14], v[15], 0x5410)));
    };
    auto pace = [&](unsigned t) { unsigned c; do { asm volatile("mov.u32 %0, %%clock;" : "=r"(c)); } while (c - clk0 < t); };
    if (warp == 7) {
        TSW(7, 2); TSQ(1);
        if (lane == 0) {
            asm volatile("prefetch.tensormap [%0];" ::"l"(&tmx) : "memory");
            asm volatile("prefetch.tensormap [%0];" ::"l"(&tmx64) : "memory");
        }
        __syncwarp();
        TSW(7, 13); TSQ(3);
        auto xh = [&](int s, int w, uint32_t bar) {
            e_tma(bar, &tmx64, sbase + OFF_X + s * X_BYTES + w * 16384, s * BK, mt * BM + w * 128);
            e_tma(bar, &tmx64, sbase + OFF_X + s * X_BYTES + w * 16384 + 8192, s * BK, mt * BM + w * 128 + 64);
        };
        pace(PX0);
        if (XS & 1) { e_expect(bars + 8 * B_FULL, X_BYTES / 2); xh(0, 0, bars + 8 * B_FULL); }
        else { e_expect(bars + 8 * B_FULL, X_BYTES); issue_x(0, 0); }
        TSQ(4);
        if (R1MODE == 4) {
            pace(PR1);
#pragma unroll
            for (int c = 0; c < 4; c++) load_blk(1, c);
            cp_commit();
        }
        target = ld_flag(myflags + 6);
        TSW(7, 1);
        pace(PR2);
        load_blk(2, 3);
        cp_commit();
        mbar_wait(bars + 8 * B_LUT);
        if (R1MODE == 4) {
            uint32_t c[32];
            cp_wait<1>();
            __syncwarp();
#pragma unroll
            for (int i = 0; i < 32; i++) c[i] = lds32(sbase + OFF_STG + (i >> 3) * 4096 + 1024 + (i & 7) * 128 + fl * 4);
#pragma unroll
            for (int i = 0; i < 32; i++) c[i] = lds32(sbase + OFF_LUT + (i >> 3) * 2048 + lane * 4 + c[i] * 128);
            uint4* dst = ptr_add(wscr, (uint32_t)(((g * 128 + 8 + mt) * BN + lane) * 16));
#pragma unroll
            for (int b = 0; b < 4; b++)
                stg128(dst + b * 32, make_uint4(prmt(c[8 * b], c[8 * b + 1], 0x5410), prmt(c[8 * b + 2], c[8 * b + 3], 0x5410),
                                                prmt(c[8 * b + 4], c[8 * b + 5], 0x5410), prmt(c[8 * b + 6], c[8 * b + 7], 0x5410)));
            TSW(7, 14);
        }
        if (XS & 1) { pace(PX0B); e_expect(bars + 8 * B_L, X_BYTES / 2); xh(0, 1, bars + 8 * B_L); }
        target = (target | 7) + 1;
        if (PFX > 100) { pace(PFX); pf_x(PFXB + (g >> 2), mt * BM + (g & 3) * 64); }
        if (PX1 < 100000) { pace(PX1); issue_x(1, 1); }
        if (F2POS == 0) { cp_wait<0>(); __syncwarp(); foreign(2); }
        mbar_wait(bars + 8 * B_FULL);
        if (PX1 == 100000) { if (XS & 2) xh(1, 0, bars + 8 * (B_FULL + 1)); else issue_x(1, 1); }
        if (PFX == 1) pf_x(PFXB + (g >> 2), mt * BM + (g & 3) * 64);
        if (F2POS == 1) { cp_wait<0>(); __syncwarp(); foreign(2); }
        if (W1BY == 7) {
            if (W1D) { unsigned c, c0; asm volatile("mov.u32 %0, %%clock;" : "=r"(c0)); do { asm volatile("mov.u32 %0, %%clock;" : "=r"(c)); } while (c - c0 < W1D); }
            e_bulk_p(1, bars + 8 * (B_FULL + 1), W_BYTES, sbase + OFF_W + W_BYTES, wgrp + 8 * BN);
            TSW(7, 4);
        }
        if (PX1 == 100001) issue_x(1, 1);
        if (F2POS == 2) { cp_wait<0>(); __syncwarp(); foreign(2); }
        if (PFX == 2) pf_x(PFXB + (g >> 2), mt * BM + (g & 3) * 64);
        TSW(7, 3);
    } else {
        if (wg == 1 && sl >= NOW) { pace(PSBASE + sl * PSTEP); load_slab(); }
        auto init6 = [&](auto wc) {
            constexpr int w = decltype(wc)::value;
#pragma unroll
            for (int i = 0; i < 6; i++) { constexpr int b0 = 1 + w * 6; if (b0 + i < B_SLAB) mbar_init(bars + 8 * (b0 + i), b0 + i <= B_L + 3 ? 1 : 7); }
#pragma unroll
            for (int i = 0; i < 6; i++) {
                constexpr int b0 = 1 + w * 6;
                if (b0 + i < B_XV) asm volatile("mbarrier.arrive.expect_tx.shared::cta.b64 _, [%0], %1;" ::"r"(bars + 8 * (b0 + i)), "n"(X_BYTES + W_BYTES) : "memory");
            }
        };
        auto init_bars = [&]() {
            if (lane == 0) {
#pragma unroll
                for (int i = 0; i < 6; i++) {
                    const int b = 1 + warp * 6 + i;
                    if (b < B_SLAB) mbar_init(bars + 8 * b, b <= B_L + 3 ? 1 : 7);
                    if (b < B_XV) asm volatile("mbarrier.arrive.expect_tx.shared::cta.b64 _, [%0], %1;" ::"r"(bars + 8 * b), "r"(((XS & 2) && b == 1 ? X_BYTES / 2 : X_BYTES) + W_BYTES) : "memory");
                }
                asm volatile("fence.mbarrier_init.release.cluster;" ::: "memory");
            }
            __syncwarp();
        };
        if (R1PRE) { pace(PR1); load_blk(1, warp); cp_commit(); }
        init_bars();
        if (!R1PRE) { pace(PR1); load_blk(1, warp); cp_commit(); }
        TSW(0, 15);
        uint32_t lv[16], v[32], T[8];
        cp_wait<1>();
        __syncwarp();
#pragma unroll
        for (int i = 0; i < 16; i++) asm volatile("ld.shared.u16 %0, [%1];" : "=r"(lv[i]) : "r"(stg + i * 64 + fl * 2));
#pragma unroll
        for (int i = 0; i < 16; i++) lv[i] = lv[i] ? lv[i] : 0x8000u;
#pragma unroll
        for (int i = 0; i < 4; i++) {
            const uint32_t p01 = prmt(lv[4 * i], lv[4 * i + 1], 0x5140u), p23 = prmt(lv[4 * i + 2], lv[4 * i + 3], 0x5140u);
            T[i] = prmt(p01, p23, 0x5410u); T[4 + i] = prmt(p01, p23, 0x7632u);
        }
        TSW(0, 7);
#pragma unroll
        for (int i = 0; i < 16; i++) sts32(lut_a + i * 128, lv[i]);
        __syncwarp();
        e_arrive(bars + 8 * B_LUT);
        auto more_raw = [&](int j) {
            if (R2AT == j && wg == 1) { load_blk(2, warp); load_blk(2, warp - 4); cp_commit(); }
            if (R3AT == j && wg == 0) load_raw(3);
            if (R3W1 == j && wg == 1) load_raw(3);
        };
        auto own_task = [&](int t) {
            __syncwarp();
            uint32_t c[8];
#pragma unroll
            for (int i = 0; i < 8; i++) c[i] = lds32(stg + t * 1024 + fl * 4 + i * 128);
            uint4 o = lookup8_reg(c, T, two31);
            stg128(my_unit(t), o);
            if (t == 1) { TSW(4, 6); if (R1MODE != 4) TSW(0, 14); }
        };
        auto raw1_task = [&]() {
            if (wg == 1) cp_wait<(R2AT < 4) + (R3W1 < 4)>(); else cp_wait<(R3AT < 4)>();
            own_task(1);
        };
        auto piece_ld = [&](int j) {
            TSP(j * 8);
            mbar_wait(bars + 8 * (B_SLAB + j));
            TSP(j * 8 + 1);
#pragma unroll
            for (int i = 0; i < 16; i++) v[(j & 1) * 16 + i] = lds32(sbase + (j < 2 ? OFF_SLAB0 : OFF_SLAB2) + (j & 1) * SLAB_BYTES + i * (BN * 4) + (warp * 32 + fl) * 4);
            more_raw(j);
        };
        auto piece_st = [&](int j) {
            const uint32_t dst = sbase + OFF_W + j * 2 * CHUNK_BYTES + (warp * 32 + lane) * 16;
            sts128(dst, lookup8_reg(v + (j & 1) * 16, T, two31));
            sts128(dst + CHUNK_BYTES, lookup8_reg(v + (j & 1) * 16 + 8, T, two31));
            TSP(j * 8 + 2);
            TSW(PW, 8 + j);
        };
        if (R2AT < 0 && wg == 1) { pace(PR2); more_raw(R2AT); }
        piece_ld(0);
        if (PIPE & 1) piece_ld(1);
        piece_st(0);
        if (!(PIPE & 1)) piece_ld(1);
        if (PIPE & 2) piece_ld(2);
        piece_st(1);
        if (!(PIPE & 2)) piece_ld(2);
        if (PIPE & 4) piece_ld(3);
        piece_st(2);
        if (!(PIPE & 4)) piece_ld(3);
        if (R1MODE == 2 || (R1MODE == 3 && wg == 0)) raw1_task();
        piece_st(3);
        asm volatile("fence.proxy.async.shared::cta;" ::: "memory");
        TSP(27);
        __syncwarp();
        e_arrive(bars + 8 * B_FULL);
        if (R1MODE == 1 || (wg == 1 && R1MODE >= 3)) raw1_task();
        more_raw(4);
        if (wg == 1) {
            cp_wait<(R3W1 < 5)>();
            own_task(2);
            if (R34AT == 0) { if (R3W1 == 5) load_raw(3); load_raw(4); }
            mbar_wait(bars + 8 * B_LUT);
            foreign(2);
            if (R34AT == 1) { if (R3W1 == 5) load_raw(3); load_raw(4); }
        }
        TSW(4, 12);
    }

    float acc0[112], acc1[112];
    const uint64_t descA_hi = ((uint64_t)1 << 62) | ((uint64_t)(1024 >> 4) << 32) | ((uint64_t)1 << 16);
    const uint64_t descB_hi = ((uint64_t)(128 >> 4) << 32) | ((uint64_t)(CHUNK_BYTES >> 4) << 16);
    const uint32_t a16 = ((sbase & 0x3FFFF) >> 4) + wg * 1024 + (uint32_t)descA_hi, b16w = (((sbase + OFF_W) & 0x3FFFF) >> 4) + (uint32_t)descB_hi;
    auto dscA = [&](uint32_t lo) { return (descA_hi & 0xFFFFFFFF00000000ull) | lo; };
    auto dscB = [&](uint32_t lo) { return (descB_hi & 0xFFFFFFFF00000000ull) | lo; };
    uint32_t xo = 0, wo = 0, wo_prev = 2 * W_BYTES;
    const uint4* wnext = wgrp + 2 * 8 * BN;
    auto validate = [&](int t, uint32_t wofs) {
        constexpr int NV = VSPLIT == 1 ? 7 : 14;
        const uint32_t u = VSPLIT == 1 ? tid + wg * (W_BYTES / 32 - 128) : tid & 127;
        const uint32_t a = sbase + OFF_W + wofs + u * 16;
        for (int n = 0; n < 2000000; n++) {
            uint32_t m = 0xffffffffu;
#pragma unroll
            for (int i = 0; i < 7; i++) m = min(m, lds32(a + u * 16 + (lane >> 2) * 4 + i * 4096));
            if (__all_sync(0xffffffff, m != 0)) break;
            const uint4* src = ptr_add(wgrp, (uint32_t)((t * 8 * BN + (u & ~31) * 2 + lane) * 16));
#pragma unroll 1
            for (int i = 0; i < 14; i++) cp16(sbase + OFF_W + wofs + ((u & ~31) * 2 + lane + (i >> 1) * 256 + (i & 1) * 32) * 16, src + (i >> 1) * 256 + (i & 1) * 32);
            cp_commit();
            cp_wait<0>();
            asm volatile("fence.proxy.async.shared::cta;" ::: "memory");
            __syncwarp();
        }
    };
    auto batch = [&](int s, bool val) {
        if (val && s == 0) TSP(28);
        mbar_wait(bars + 8 * (B_FULL + s));
        if (val && s == 0) TSP(29);
        if (wg == 1 && s < 2 && ((XS >> s) & 1)) mbar_wait(bars + 8 * (B_L + 3 * s));
        if (val && VSPLIT != 2 && wg == 0 && (unsigned)(s - 1) < NFAST) validate(s, wo);
        if (s + wg > 0) asm volatile("bar.sync %0, 256;" ::"r"(2 + wg) : "memory");
        TSW(0, 16 + s); TSW(4, 48 + s); TS8(16 + s);
        const uint32_t al = a16 + (xo >> 4), bl = b16w + (wo >> 4);
        wgmma_fence();
#pragma unroll
        for (int kk = 0; kk < 4; kk++) {
            const uint64_t db = dscB(bl + kk * (2 * CHUNK_BYTES >> 4));
            wgmma_m64n224k16(acc0, dscA(al + kk * 2), db, (s | kk) != 0);
            wgmma_m64n224k16(acc1, dscA(al + kk * 2 + (8192 >> 4)), db, (s | kk) != 0);
        }
        wgmma_commit();
        if (val && VSPLIT && wg == 1 && s < NFAST) { mbar_wait(bars + 8 * (B_FULL + s + 1)); validate(s + 1, 3 * W_BYTES - wo - wo_prev); }
        asm volatile("bar.arrive %0, 256;" ::"r"(3 - wg) : "memory");
        TSW(0, 32 + s); TSW(4, 64 + s);
    };
    auto advance = [&]() {
        wo_prev = wo;
        xo = xo == 2 * X_BYTES ? 0 : xo + X_BYTES;
        wo = wo == 2 * W_BYTES ? 0 : wo + W_BYTES;
        wnext += 8 * BN;
    };
    if (PEEL) batch(0, false);
#pragma unroll 1
    for (int s = 0; s < 9; s++) {
        if (!PEEL) batch(s, true);
        const uint32_t bs = bars + 8 * s;
        if (warp == 7) {
            const int fb = (int)(W_FLAG >> (4 * s)) & 15;
            unsigned* fp = ptr_add(myflags, fb * 4);
            unsigned fv = target;
            const int pb = round_batch(s);
            const uint32_t l1 = (L1_MASK >> s) & 1, l2 = (L2_MASK >> s) & 1;
            if (fb) fv = ld_flag(fp);
            else e_bulk_p(l1 && (L1PRE || !pb), bs + 8 * (B_FULL + 2), W_BYTES, sbase + OFF_W + wo_prev, wnext);
            if (s == 0) {
                if (XS & 2) {
                    e_expect(bars + 8 * (B_L + 3), X_BYTES / 2);
                    e_tma(bars + 8 * (B_L + 3), &tmx64, sbase + OFF_X + X_BYTES + 16384, BK, mt * BM + 128);
                    e_tma(bars + 8 * (B_L + 3), &tmx64, sbase + OFF_X + X_BYTES + 16384 + 8192, BK, mt * BM + 192);
                }
                if (X2POS == 0) issue_x(2, 2);
                if (PFX == 3) pf_x(PFXB + (g >> 2), mt * BM + (g & 3) * 64);
                if (W2POS == 0) {
                    if (W2D) { unsigned c, c0; asm volatile("mov.u32 %0, %%clock;" : "=r"(c0)); do { asm volatile("mov.u32 %0, %%clock;" : "=r"(c)); } while (c - c0 < W2D); }
                    e_bulk_p(1, bs + 8 * (B_FULL + 2), W_BYTES, sbase + OFF_W + wo_prev, wnext);
                }
            }
            TSW(7, 112 + s);
            if (s == 0 && X2POS == 1) issue_x(2, 2);
            if (pb) {
                mbar_wait(bars + 8 * (B_DQ + pb));
                mbar_wait(bs + 8 * B_EMPTY);
                e_publish(ptr_add(myflags, pb * 4));
                if (!L1PRE) e_bulk_p(l1, bs + 8 * (B_FULL + 2), W_BYTES, sbase + OFF_W + wo_prev, wnext);
            } else {
                if (fb) {
                    finish_poll(fp, fv, target);
                    e_bulk_p(l1, bs + 8 * (B_FULL + 2), W_BYTES, sbase + OFF_W + wo_prev, wnext);
                }
                mbar_wait(bs + 8 * B_EMPTY);
                if (s == W12_AT) {
                    issue_w(12, 3, B_WF);
                    e_bulk(bars + 8 * (B_WF + 3), W_BYTES / 2, sbase + OFF_LUT, wgrp + 15 * 8 * BN);
                }
            }
            wgmma_wait<0>();
            if (W2POS == 1) e_bulk_p(s == 0, bs + 8 * (B_FULL + 2), W_BYTES, sbase + OFF_W + wo_prev, wnext);
            e_bulk_p(l2, bs + 8 * (B_FULL + 3), W_BYTES, sbase + OFF_W + wo, wnext + 8 * BN);
            e_tma(bs + 8 * (B_FULL + 3), &tmx, sbase + OFF_X + xo, (s + 3) * BK, mt * BM);
            TSW(7, 96 + s);
        } else {
            if (s == 0) {
                if (wg == 0) {
                    if (R3AT > 4) load_raw(3);
                    if (R4W0 == 0) load_raw(4);
                    if (warp == W1BY) {
                        if (W1D) { unsigned c, c0; asm volatile("mov.u32 %0, %%clock;" : "=r"(c0)); do { asm volatile("mov.u32 %0, %%clock;" : "=r"(c)); } while (c - c0 < W1D); }
                        e_bulk_p(1, bars + 8 * (B_FULL + 1), W_BYTES, sbase + OFF_W + W_BYTES, wgrp + 8 * BN); TSW(3, 4);
                    }
                } else if (R34AT == 2) { if (R3W1 == 5) load_raw(3); load_raw(4); }
            }
            const int r = s + wg;
            if (R4W0 && r == 0) {
                cp_wait<0>();
                __syncwarp();
                stg128(my_unit(3), dequant8(stg + 3 * 1024 + fl * 4, lut_a));
                if (R4W0 == 2) mbar_wait(bars + 8 * (B_FULL + 1));
                load_raw(4); load_raw(5);
            } else if (wg == 0 && s < 2) coop(s + 3);
            else if (r < NROUNDS) { if (PAIR) coop2(2 * r + 1); else { coop(2 * r + 1); if (r < 7) coop(2 * r + 2); } }
            if (round_batch(r)) { __syncwarp(); e_arrive(bars + 8 * (B_DQ + round_batch(r))); }
            TSW(0, 80 + s);
            wgmma_wait<0>();
            if (warp == 3) e_arrive(bs + 8 * B_EMPTY);
            if (warp == 2 && (s & 3) == 1) pf_x(s + 4 + (g >> 2), mt * BM + (g & 3) * 64);
        }
        advance();
        if (PEEL) batch(s + 1, true);
    }
    auto rezero = [&]() {
        mbar_wait(bars + 8 * (B_FULL + 11));
#pragma unroll
        for (int t = 1; t <= NFAST; t++) stg128(my_unit(t), make_uint4(0, 0, 0, 0));
    };
    const int w4 = warp & 3;
    __nv_bfloat16* o = ptr_add(out, (uint32_t)(((mt * BM + wg * 128 + w4 * 16 + (lane >> 2)) * F_ + g * BN + (lane & 3) * 8) * 2));
    auto wofs = [](int st, int kk) -> uint32_t {
        return st < 15 ? OFF_W + (st == 11 ? 2 : st == 12 ? 3 : st - 13) * W_BYTES + kk * 2 * CHUNK_BYTES
                       : kk < 2 ? OFF_LUT + kk * 2 * CHUNK_BYTES : OFF_X + 2 * X_BYTES + (kk - 2) * 16384;
    };
    auto xofs = [](int st, int kk, int r) -> uint32_t {
        return (st == 11 ? 2 * X_BYTES + r * 8192 : ((st - 12) >> 1) * X_BYTES + (st & 1) * 8192) + kk * 32;
    };
    auto launder = [&]() { uint32_t b16 = (sbase & 0x3FFFF) >> 4; asm volatile("mov.u32 %0, %0;" : "+r"(b16)); return b16; };
    auto dA = [&](uint32_t b16, uint32_t ofs) { return (descA_hi & 0xFFFFFFFF00000000ull) | (uint64_t)(b16 + wg * 1024 + (ofs >> 4) + (uint32_t)descA_hi); };
    auto dB = [&](uint32_t b16, uint32_t ofs) { return (descB_hi & 0xFFFFFFFF00000000ull) | (uint64_t)(b16 + (ofs >> 4) + (uint32_t)descB_hi); };
    float p0[64], p1[32], p2[16];
    constexpr int PK0 = ASP < CSP ? ASP : CSP;
    uint32_t pk[(14 - PK0) * 4 + 1];
    auto split_acc1 = [&]() {
#pragma unroll
        for (int i = 0; i < 64; i++) asm volatile("add.f32 %0, %1, 0f00000000;" : "=f"(p0[i]) : "f"(acc1[i]));
#pragma unroll
        for (int i = 0; i < 32; i++) asm volatile("add.f32 %0, %1, 0f00000000;" : "=f"(p1[i]) : "f"(acc1[64 + i]));
#pragma unroll
        for (int i = 0; i < 16; i++) asm volatile("add.f32 %0, %1, 0f00000000;" : "=f"(p2[i]) : "f"(acc1[96 + i]));
    };
    {
        if (!PEEL) batch(9, false);
        if (warp == 7) {
            pf_x(13 + (g >> 2), mt * BM + (g & 3) * 64);
            mbar_wait(bars + 8 * (B_EMPTY + 9));
        } else if (ZPOS == 9) rezero();
        wgmma_wait<0>();
        if (warp == 3) e_arrive(bars + 8 * (B_EMPTY + 9));
        if (warp == 7) {
            issue_w(13, 0, B_WF + 1);
            e_expect(bars + 8 * B_XV, X_BYTES);
            issue_xv(12, 0, bars + 8 * B_XV); issue_xv(12, 1, bars + 8 * B_XV);
        }
        advance();
        batch(10, false);
        if (warp == 7) mbar_wait(bars + 8 * (B_EMPTY + 10)); else if (ZPOS == 10) rezero();
        wgmma_wait<0>();
        if (warp == 3) e_arrive(bars + 8 * (B_EMPTY + 10));
    }
    {
        mbar_wait(bars + 8 * (B_FULL + 11));
        asm volatile("bar.sync %0, 256;" ::"r"(2 + wg) : "memory");
        const uint32_t b16 = launder();
        wgmma_fence();
#pragma unroll
        for (int kk = 0; kk < 4; kk++) wgmma_m64n224k16(acc0, dA(b16, xofs(11, kk, 0)), dB(b16, wofs(11, kk)), 1);
        wgmma_commit();
        asm volatile("bar.arrive %0, 256;" ::"r"(3 - wg) : "memory");
        if (warp == 7) {
            issue_w(14, 1, B_WF + 2);
            e_expect(bars + 8 * (B_XV + 1), X_BYTES);
            issue_xv(13, 0, bars + 8 * (B_XV + 1)); issue_xv(13, 1, bars + 8 * (B_XV + 1));
            mbar_wait(bars + 8 * (B_EMPTY + 11));
        } else if (ZPOS == 11) rezero();
        if (!PLAG && FADDPOS == 0) split_acc1();
        wgmma_wait<0>();
        if (warp == 3) e_arrive(bars + 8 * (B_EMPTY + 11));
        if (warp == 7) {
            e_bulk(bars + 8 * (B_WF + 4), 2 * CHUNK_BYTES, sbase + wofs(15, 2), wgrp + (15 * 8 + 4) * BN);
            e_bulk(bars + 8 * (B_XV + 4), 2 * CHUNK_BYTES, sbase + wofs(15, 3), wgrp + (15 * 8 + 6) * BN);
        }
    }
    uint32_t af[80];
    const uint32_t lm = sbase + wg * 16384 + (w4 * 16 + (lane & 15)) * 128 + (((lane >> 4) ^ (lane & 7)) << 4);
    auto ldfrag = [&](int st) {
#pragma unroll
        for (int kk = 0; kk < 4; kk++) {
            uint32_t* r = af + ((st - 11) * 4 + kk) * 4;
            asm volatile("ldmatrix.sync.aligned.m8n8.x4.shared.b16 {%0,%1,%2,%3}, [%4];" : "=r"(r[0]), "=r"(r[1]), "=r"(r[2]), "=r"(r[3])
                         : "r"((lm ^ (kk << 5)) + xofs(st, 0, 1)) : "memory");
        }
    };
    {
        asm volatile("bar.sync %0, 256;" ::"r"(2 + wg) : "memory");
        TSK(0, 28); TSF(0);
        const uint32_t b16 = launder();
#pragma unroll
        for (int st = 12; st < 16; st++) {
            if (!(st & 1)) mbar_wait(bars + 8 * (B_XV + ((st - 12) >> 1)));
            mbar_wait(bars + 8 * (B_WF + st - 12));
            if (!(st & 1)) wgmma_fence();
#pragma unroll
            for (int kk = 0; kk < 4; kk++) {
                if (st == 15 && kk >= 2) mbar_wait(bars + 8 * (kk == 2 ? B_WF + 4 : B_XV + 4));
                wgmma_m64n224k16(acc0, dA(b16, xofs(st, kk, 0)), dB(b16, wofs(st, kk)), 1);
            }
            if (st & 1) wgmma_commit();
        }
        asm volatile("bar.arrive %0, 256;" ::"r"(3 - wg) : "memory");
        TSF(1);
        if (!PLAG && FADDPOS == 1) split_acc1();
        wgmma_wait<1>();
        if (w4 == 3) { e_expect(bars + 8 * (B_XV + 2 + wg), X_BYTES / 2); issue_xv(14, wg, bars + 8 * (B_XV + 2 + wg)); }
        wgmma_wait<0>();
        if (w4 == 3) { e_expect(bars + 8 * (B_X15 + wg), X_BYTES / 2); issue_xv(15, wg, bars + 8 * (B_X15 + wg)); }
        TSF(2); TS9(0);
        unsigned tb; asm volatile("mov.u32 %0, %%clock;" : "=r"(tb));
        auto pst = [&](unsigned t) { unsigned c; do { asm volatile("mov.u32 %0, %%clock;" : "=r"(c)); } while (c - tb < t); };
#pragma unroll
        for (int h = 0; h < PK0; h++) {
            if (PSTA && h >= PSF) pst((h - PSF + 1) * PSTA);
            store_half<0>(acc0, o, h);
            if (L11 == h) ldfrag(11);
            if (L12 == h) { mbar_wait(bars + 8 * (B_XV + 2 + wg)); ldfrag(12); if (L13) ldfrag(13); }
        }
#pragma unroll
        for (int h = PK0; h < 14; h++) pack_half(acc0, h, pk + (h - PK0) * 4);
#pragma unroll
        for (int h = PK0; h < (ASP > CSP ? ASP : CSP); h++) { if (PSTA && wg == (ASP > CSP ? 0 : 1)) pst((h - PSF + 1) * PSTA); store_packed(o, h, pk + (h - PK0) * 4, ASP > CSP ? wg ^ 1 : wg); }
        TSF(3);
    }
    {
        if (L11 < 0) ldfrag(11);
        asm volatile("bar.sync %0, 256;" ::"r"(2 + wg) : "memory");
        TSF(4);
        const uint32_t b16 = launder();
#pragma unroll
        for (int st = 11; st < 16; st++) {
            wgmma_fence();
#pragma unroll
            for (int kk = 0; kk < 4; kk++) {
                const int i = (st - 11) * 4 + kk;
                wgmma_rs_n128(p0, af + i * 4, dB(b16, wofs(st, kk)));
                if (i == 0) TS9(1);
                constexpr int PD = L12 < 0 ? 1 : 2 + L13;
                if (kk == 0 && st + PD < 16) {
                    if (st == 11 && L12 < 0) mbar_wait(bars + 8 * (B_XV + 2 + wg));
                    if (st + PD == 14) mbar_wait(bars + 8 * (B_X15 + wg));
                    ldfrag(st + PD);
                }
                if (i % ISTEP == 0) {
                    const int h0 = ASP + i / ISTEP, h1 = CSP + i / ISTEP;
                    if (ASP == CSP) { if (h0 < 14) store_packed(o, h0, pk + (h0 - PK0) * 4, 1); }
                    else {
                        if (h0 < 14) store_packed(o, h0, pk + (h0 - PK0) * 4, wg ^ 1);
                        if (h1 < 14) store_packed(o, h1, pk + (h1 - PK0) * 4, wg);
                    }
                }
            }
        }
        wgmma_commit();
        asm volatile("bar.arrive %0, 256;" ::"r"(3 - wg) : "memory");
        TSF(5); TS9(2);
        if (PLAG && warp == 5) e_tma(bars + 8 * (B_L + 3), &tmx64, sbase + OFF_X + 2 * X_BYTES + 8192 + 16384, 10 * BK, mt * BM + 128 + 64);
        wgmma_wait<0>();
        TSF(6); TS9(3);
        if (PLAG && wg == 0) {
            if (w4 < 2) e_bulk_p(1, bars + 8 * B_L, W_BYTES / 2, sbase + OFF_X + w4 * X_BYTES, wgrp + (10 * 8 + w4 * 4) * BN);
            else if (w4 == 2) e_tma(bars + 8 * B_L, &tmx64, sbase + OFF_X + 2 * X_BYTES + 8192, 10 * BK, mt * BM + 64);
        }
        unsigned tb; asm volatile("mov.u32 %0, %%clock;" : "=r"(tb));
        auto pst = [&](unsigned t) { unsigned c; do { asm volatile("mov.u32 %0, %%clock;" : "=r"(c)); } while (c - tb < t); };
#pragma unroll
        for (int h = 0; h < (BSP > DSP ? BSP : DSP); h++) {
            if (h < BSP && h < DSP) { if (PSTB && wg == 0) pst(PSB0 + h * PSTB); if (PSTD && wg == 1) pst(h * PSTD); store_half<64 * F_>(p0, o, h); }
            else if (wg == (BSP > DSP ? 0 : 1)) { if (PSTB && wg == 0) pst(PSB0 + h * PSTB); store_half<64 * F_>(p0, o, h); }
        }
        TSF(7);
    }
    {
        if (PLAG == 1 || (PLAG == 3 && wg == 1)) { mbar_wait(bars + 8 * B_L); if (wg == 1) mbar_wait(bars + 8 * (B_L + 3)); }
        asm volatile("bar.sync %0, 256;" ::"r"(2 + wg) : "memory");
        TSF(8);
        const uint32_t b16 = launder();
        wgmma_fence();
#pragma unroll
        for (int i = 0; i < 20; i++) {
            wgmma_rs_n64(p1, af + i * 4, dB(b16, wofs(11 + (i >> 2), i & 3) + 128 * 16));
            if (i % ISTEP2 == 0) {
                const int h0 = BSP + i / ISTEP2, h1 = DSP + i / ISTEP2;
                if (BSP == DSP) { if (h0 < 8) store_half<64 * F_>(p0, o, h0); }
                else {
                    if (h0 < 8) store_half<64 * F_>(p0, o, h0, wg ^ 1);
                    if (h1 < 8) store_half<64 * F_>(p0, o, h1, wg);
                }
            }
        }
        if (PLAG) {
            if (PLAG == 2 || (PLAG == 3 && wg == 0)) { mbar_wait(bars + 8 * B_L); if (wg == 1) mbar_wait(bars + 8 * (B_L + 3)); }
#pragma unroll
            for (int kk = 0; kk < 4; kk++) wgmma_ss_n64(p1, dA(b16, xofs(11, kk, 1)), dB(b16, OFF_X + (kk >> 1) * X_BYTES + (kk & 1) * 2 * CHUNK_BYTES + 128 * 16));
        }
        wgmma_commit();
        if (PLAG) {
#pragma unroll
            for (int kk = 0; kk < 4; kk++) wgmma_ss_n32(p2, dA(b16, xofs(11, kk, 1)), dB(b16, OFF_X + (kk >> 1) * X_BYTES + (kk & 1) * 2 * CHUNK_BYTES + 192 * 16));
        }
#pragma unroll
        for (int i = 0; i < 20; i++) {
            wgmma_rs_n32(p2, af + i * 4, dB(b16, wofs(11 + (i >> 2), i & 3) + 192 * 16));
            if (i == NP2 - 1) {
                wgmma_commit();
                wgmma_wait<1>();
                TS9(4);
#pragma unroll
                for (int h = 0; h < 4; h++) store_half<64 * F_ + 128>(p1, o, h, NP2W == 2 ? 1 : wg);
                wgmma_fence();
            }
        }
        wgmma_commit();
        if (wg == 0) asm volatile("bar.arrive 3, 256;" ::: "memory");
        TSF(9);
        if (!NP2) { wgmma_wait<1>(); TS9(4); }
        if (!NP2 || (NP2W == 1 && wg == 0)) store_tile<64 * F_ + 128, 0, 2>(p1, o);
        wgmma_wait<0>();
        TSK(4, 63); TSF(10);
        store_tile<64 * F_ + 192, 0, 1>(p2, o);
        TSK(4, 77); TSF(11);
    }
}

typedef CUresult (*EncodeTiledFn)(CUtensorMap*, CUtensorMapDataType, cuuint32_t, void*, const cuuint64_t*, const cuuint64_t*, const cuuint32_t*, const cuuint32_t*, CUtensorMapInterleave, CUtensorMapSwizzle, CUtensorMapL2promotion, CUtensorMapFloatOOBfill);

extern "C" void kernel_launch(void* const* d_in, const int* in_sizes, int n_in, void* d_out, int out_size) {
    static EncodeTiledFn enc = nullptr;
    static decltype(&fused_kernel<true>) kern = nullptr;
    static void *p_w = nullptr, *p_flags = nullptr, *p_prof = nullptr;
    if (!enc) {
        void* fn = nullptr; cudaDriverEntryPointQueryResult qr;
        cudaGetDriverEntryPoint("cuTensorMapEncodeTiled", &fn, cudaEnableDefault, &qr);
        enc = (EncodeTiledFn)fn;
        int dev = 0, rsv = 0;
        cudaGetDevice(&dev);
        cudaDeviceGetAttribute(&rsv, cudaDevAttrReservedSharedMemoryPerBlock, dev);
        kern = HARDBASE && rsv == 1024 ? fused_kernel<true> : fused_kernel<false>;
        cudaFuncSetAttribute(kern, cudaFuncAttributeMaxDynamicSharedMemorySize, SMEM_BYTES);
        cudaGetSymbolAddress(&p_w, g_w);
        cudaGetSymbolAddress(&p_flags, g_flags);
    }
    CUtensorMap tmx, tmx64, tmq;
    {
        cuuint64_t gdim[2] = {(cuuint64_t)F_, (cuuint64_t)D_};
        cuuint64_t gstr[1] = {(cuuint64_t)F_ * 4};
        cuuint32_t box[2] = {(cuuint32_t)BN, 16};
        cuuint32_t estr[2] = {1, 1};
        enc(&tmq, CU_TENSOR_MAP_DATA_TYPE_INT32, 2, d_in[1], gdim, gstr, box, estr, CU_TENSOR_MAP_INTERLEAVE_NONE,
            CU_TENSOR_MAP_SWIZZLE_NONE, CU_TENSOR_MAP_L2_PROMOTION_L2_128B, CU_TENSOR_MAP_FLOAT_OOB_FILL_NONE);
    }
    {
        cuuint64_t gdim[2] = {(cuuint64_t)D_, (cuuint64_t)S_};
        cuuint64_t gstr[1] = {(cuuint64_t)D_ * 2};
        cuuint32_t box[2] = {(cuuint32_t)BK, (cuuint32_t)BM};
        cuuint32_t estr[2] = {1, 1};
        enc(&tmx, CU_TENSOR_MAP_DATA_TYPE_BFLOAT16, 2, d_in[0], gdim, gstr, box, estr, CU_TENSOR_MAP_INTERLEAVE_NONE,
            CU_TENSOR_MAP_SWIZZLE_128B, XPROMO, CU_TENSOR_MAP_FLOAT_OOB_FILL_NONE);
        box[1] = 64;
        enc(&tmx64, CU_TENSOR_MAP_DATA_TYPE_BFLOAT16, 2, d_in[0], gdim, gstr, box, estr, CU_TENSOR_MAP_INTERLEAVE_NONE,
            CU_TENSOR_MAP_SWIZZLE_128B, XPROMO, CU_TENSOR_MAP_FLOAT_OOB_FILL_NONE);
    }
    kern<<<128, 256, SMEM_BYTES>>>((const int*)d_in[1], (const unsigned short*)d_in[2], (__nv_bfloat16*)d_out, (uint4*)p_w, (unsigned*)p_flags, 0x80000000u, tmq, tmx64, tmx
    );
    (void)p_prof;
}
```

```cpp
#include <cuda_runtime.h>
#include <cuda_bf16.h>
#include <cuda.h>
#include <stdint.h>
#include <stdio.h>

#define LA 2
#define XPROMO CU_TENSOR_MAP_L2_PROMOTION_L2_128B
#define CSPLIT 5
#define FADDPOS 1
#define BSPLIT 4
#define DSPLIT 4
#define FLAGPOS 1
#define RAW1POS 5
#define PIPE 6
#define PR1 1100
#define LK 1
#define PX0 1150
#define PX1 100000
#define R2AT 0
#define R3AT 3
#define R4AT 4
#define W1EARLY 1
#define PR2 1700
#define PSTEP 0
#define PSBASE 0
#define NOW 2
#define R34AT 0
#define R1MODE 1
#define ST2 1
#define PR34 3500
#define DEADT 300
#define PPOLL 2800
#define ALLONLY 0
#define X1POST 0
#define W3FIRST 1
#define W1BY 3
#define W1D 150
#define F2POS 1
#define W2POS 0
#define W2D 200
#define W3D 0
#define W4L2 0
#define R3W1 4
#define VGRAN 32
#define X2POS 0
#define VSPLIT 0
#define NF 4
#define PAIR 0
#define ZPOS 10
#define PFX 0
#define PFXB 2
#define ASP 10
#define CSP 10
#define BSP 8
#define DSP 5
#define ISTEP 2
#define ISTEP2 2
#define PEEL 1
#define ILV 0
#define R4W0 0
#define PLAG 0
#define PSTA 110
#define PSF 2
#define PSTB 110
#define PSB0 200
#define L11 4
#define L12 7
#define L13 0
#define NP2 0
#define NP2W 1
#define PSTD 100
#define FASTINIT 0
#define R1PRE 0
#define L1PRE 1
#define XS 1
#define PX0B 2700
#define X15AT -1
#define ALT 1
#define ALTS 4
#define HARDBASE 1

constexpr int S_ = 2048, D_ = 1024, F_ = 3584;
constexpr int BM = 256, BN = 224, BK = 64;
constexpr int X_BYTES = BM * BK * 2;
constexpr int W_BYTES = BN * BK * 2;
constexpr int CHUNK_BYTES = BN * 16;
constexpr int OFF_X = 0;
constexpr int OFF_W = 3 * X_BYTES;
constexpr int OFF_STG = OFF_W + 3 * W_BYTES;
constexpr int OFF_LUT = OFF_W + 4 * W_BYTES;
constexpr int OFF_BAR = OFF_LUT + 7 * 2048;
constexpr int OFF_PROF = OFF_BAR + 1024;
constexpr int SMEM_BYTES = OFF_PROF + 1024 + 1024;
constexpr int B_FULL = 0;
constexpr int B_XV = 12;
constexpr int B_WF = 17;
constexpr int B_EMPTY = 22;
constexpr int B_DQ = 34;
constexpr int B_SLAB = 42;
constexpr int B_L = 34;
constexpr int B_X15 = 35;
constexpr int B_LUT = 46;

__device__ __align__(1024) uint4 g_w[(size_t)F_ * D_ / 8];
__device__ __align__(128) unsigned g_flags[16 * 32];

__device__ __forceinline__ uint32_t smem_u32(const void* p) { return (uint32_t)__cvta_generic_to_shared(p); }
__device__ __forceinline__ void mbar_init(uint32_t bar, uint32_t cnt) { asm volatile("mbarrier.init.shared::cta.b64 [%0], %1;" ::"r"(bar), "r"(cnt) : "memory"); }
__device__ __forceinline__ void mbar_wait(uint32_t bar) {
    asm volatile("{\n.reg .pred p;\nWAIT_LOOP:\nmbarrier.try_wait.parity.shared::cta.b64 p, [%0], 0;\n@p bra WAIT_DONE;\nbra WAIT_LOOP;\nWAIT_DONE:\n}" ::"r"(bar) : "memory");
}
__device__ __forceinline__ void e_arrive(uint32_t bar) {
    asm volatile("{\n.reg .pred p;\nelect.sync _|p, 0xffffffff;\n@p mbarrier.arrive.shared::cta.b64 _, [%0];\n}" ::"r"(bar) : "memory");
}
__device__ __forceinline__ void e_expect(uint32_t bar, uint32_t bytes) {
    asm volatile("{\n.reg .pred p;\nelect.sync _|p, 0xffffffff;\n@p mbarrier.arrive.expect_tx.shared::cta.b64 _, [%0], %1;\n}" ::"r"(bar), "r"(bytes) : "memory");
}
__device__ __forceinline__ void e_tma(uint32_t bar, const CUtensorMap* tm, uint32_t d0, int x0, int y0) {
    asm volatile("{\n.reg .pred p;\nelect.sync _|p, 0xffffffff;\n"
                 "@p cp.async.bulk.tensor.2d.shared::cluster.global.mbarrier::complete_tx::bytes [%2], [%1, {%3, %4}], [%0];\n}"
                 ::"r"(bar), "l"(tm), "r"(d0), "r"(x0), "r"(y0) : "memory");
}
__device__ __forceinline__ void e_bulk(uint32_t bar, uint32_t bytes, uint32_t dst, const void* src) {
    asm volatile("{\n.reg .pred p;\nelect.sync _|p, 0xffffffff;\n"
                 "@p mbarrier.arrive.expect_tx.shared::cta.b64 _, [%0], %1;\n"
                 "@p cp.async.bulk.shared::cluster.global.mbarrier::complete_tx::bytes [%2], [%3], %1, [%0];\n}"
                 ::"r"(bar), "r"(bytes), "r"(dst), "l"(src) : "memory");
}
__device__ __forceinline__ void e_bulk_p(uint32_t on, uint32_t bar, uint32_t bytes, uint32_t dst, const void* src) {
    if (on) asm volatile("{\n.reg .pred p;\nelect.sync _|p, 0xffffffff;\n"
                         "@p cp.async.bulk.shared::cluster.global.mbarrier::complete_tx::bytes [%2], [%3], %1, [%0];\n}"
                         ::"r"(bar), "r"(bytes), "r"(dst), "l"(src) : "memory");
}
__device__ __forceinline__ void e_prefetch2d(const CUtensorMap* tm, int x, int y) {
    asm volatile("{\n.reg .pred p;\nelect.sync _|p, 0xffffffff;\n@p cp.async.bulk.prefetch.tensor.2d.L2.global [%0, {%1, %2}];\n}" ::"l"(tm), "r"(x), "r"(y) : "memory");
}
#define FASTREL 0
__device__ __forceinline__ void e_publish(unsigned* flag) {
    asm volatile("{\n.reg .pred p;\nelect.sync _|p, 0xffffffff;\n@p red.release.gpu.global.add.u32 [%0], 1;\n}" ::"l"(flag) : "memory");
}
__device__ __forceinline__ void e_red(unsigned* flag, unsigned v) {
    asm volatile("{\n.reg .pred p;\nelect.sync _|p, 0xffffffff;\n@p red.relaxed.gpu.global.add.u32 [%0], %1;\n}" ::"l"(flag), "r"(v) : "memory");
}
__device__ __forceinline__ bool mbar_test(uint32_t bar) {
    uint32_t r;
    asm volatile("{\n.reg .pred p;\nmbarrier.test_wait.parity.shared::cta.b64 p, [%1], 0;\nselp.u32 %0, 1, 0, p;\n}" : "=r"(r) : "r"(bar) : "memory");
    return __all_sync(0xffffffff, r != 0);
}
template <int V> struct IC { static constexpr int value = V; };
__device__ __forceinline__ unsigned ld_flag(const unsigned* f) { unsigned v; asm volatile("ld.relaxed.gpu.global.u32 %0, [%1];" : "=r"(v) : "l"(f) : "memory"); return v; }
__device__ __forceinline__ void finish_poll(const unsigned* f, unsigned v, unsigned target) {
    int n = 0;
    while (!__all_sync(0xffffffff, (int)(v - target) >= 0) && ++n < 4000000) v = ld_flag(f);
    asm volatile("fence.acquire.gpu;" ::: "memory");
    asm volatile("fence.proxy.async.global;" ::: "memory");
}
template <typename T> __device__ __forceinline__ T* ptr_add(T* base, uint32_t off) {
    uint64_t r;
    asm("{\n.reg .u32 l, h;\nmov.b64 {l, h}, %1;\nadd.cc.u32 l, l, %2;\naddc.u32 h, h, 0;\nmov.b64 %0, {l, h};\n}" : "=l"(r) : "l"(base), "r"(off));
    return (T*)r;
}
__device__ __forceinline__ void wgmma_fence() { asm volatile("wgmma.fence.sync.aligned;" ::: "memory"); }
__device__ __forceinline__ void wgmma_commit() { asm volatile("wgmma.commit_group.sync.aligned;" ::: "memory"); }
template <int N> __device__ __forceinline__ void wgmma_wait() { asm volatile("wgmma.wait_group.sync.aligned %0;" ::"n"(N) : "memory"); }
__device__ __forceinline__ void wgmma_m64n224k16(float (&d)[112], uint64_t da, uint64_t db, int scale_d) {
    asm volatile(
        "{\n.reg .pred p;\nsetp.ne.b32 p, %114, 0;\n"
        "wgmma.mma_async.sync.aligned.m64n224k16.f32.bf16.bf16 "
        "{%0, %1, %2, %3, %4, %5, %6, %7, %8, %9, %10, %11, %12, %13, %14, %15, "
        "%16, %17, %18, %19, %20, %21, %22, %23, %24, %25, %26, %27, %28, %29, %30, %31, "
        "%32, %33, %34, %35, %36, %37, %38, %39, %40, %41, %42, %43, %44, %45, %46, %47, "
        "%48, %49, %50, %51, %52, %53, %54, %55, %56, %57, %58, %59, %60, %61, %62, %63, "
        "%64, %65, %66, %67, %68, %69, %70, %71, %72, %73, %74, %75, %76, %77, %78, %79, "
        "%80, %81, %82, %83, %84, %85, %86, %87, %88, %89, %90, %91, %92, %93, %94, %95, "
        "%96, %97, %98, %99, %100, %101, %102, %103, %104, %105, %106, %107, %108, %109, %110, %111}, "
        "%112, %113, p, 1, 1, 0, 0;\n}\n"
        : "+f"(d[0]), "+f"(d[1]), "+f"(d[2]), "+f"(d[3]), "+f"(d[4]), "+f"(d[5]), "+f"(d[6]), "+f"(d[7]),
          "+f"(d[8]), "+f"(d[9]), "+f"(d[10]), "+f"(d[11]), "+f"(d[12]), "+f"(d[13]), "+f"(d[14]), "+f"(d[15]),
          "+f"(d[16]), "+f"(d[17]), "+f"(d[18]), "+f"(d[19]), "+f"(d[20]), "+f"(d[21]), "+f"(d[22]), "+f"(d[23]),
          "+f"(d[24]), "+f"(d[25]), "+f"(d[26]), "+f"(d[27]), "+f"(d[28]), "+f"(d[29]), "+f"(d[30]), "+f"(d[31]),
          "+f"(d[32]), "+f"(d[33]), "+f"(d[34]), "+f"(d[35]), "+f"(d[36]), "+f"(d[37]), "+f"(d[38]), "+f"(d[39]),
          "+f"(d[40]), "+f"(d[41]), "+f"(d[42]), "+f"(d[43]), "+f"(d[44]), "+f"(d[45]), "+f"(d[46]), "+f"(d[47]),
          "+f"(d[48]), "+f"(d[49]), "+f"(d[50]), "+f"(d[51]), "+f"(d[52]), "+f"(d[53]), "+f"(d[54]), "+f"(d[55]),
          "+f"(d[56]), "+f"(d[57]), "+f"(d[58]), "+f"(d[59]), "+f"(d[60]), "+f"(d[61]), "+f"(d[62]), "+f"(d[63]),
          "+f"(d[64]), "+f"(d[65]), "+f"(d[66]), "+f"(d[67]), "+f"(d[68]), "+f"(d[69]), "+f"(d[70]), "+f"(d[71]),
          "+f"(d[72]), "+f"(d[73]), "+f"(d[74]), "+f"(d[75]), "+f"(d[76]), "+f"(d[77]), "+f"(d[78]), "+f"(d[79]),
          "+f"(d[80]), "+f"(d[81]), "+f"(d[82]), "+f"(d[83]), "+f"(d[84]), "+f"(d[85]), "+f"(d[86]), "+f"(d[87]),
          "+f"(d[88]), "+f"(d[89]), "+f"(d[90]), "+f"(d[91]), "+f"(d[92]), "+f"(d[93]), "+f"(d[94]), "+f"(d[95]),
          "+f"(d[96]), "+f"(d[97]), "+f"(d[98]), "+f"(d[99]), "+f"(d[100]), "+f"(d[101]), "+f"(d[102]), "+f"(d[103]),
          "+f"(d[104]), "+f"(d[105]), "+f"(d[106]), "+f"(d[107]), "+f"(d[108]), "+f"(d[109]), "+f"(d[110]), "+f"(d[111])
        : "l"(da), "l"(db), "r"(scale_d));
}

__device__ __forceinline__ void wgmma_rs_n32(float (&d)[16], const uint32_t* a, uint64_t db) {
    asm volatile("wgmma.mma_async.sync.aligned.m64n32k16.f32.bf16.bf16 {%0, %1, %2, %3, %4, %5, %6, %7, %8, %9, %10, %11, %12, %13, %14, %15}, {%16, %17, %18, %19}, %20, 1, 1, 1, 0;"
        : "+f"(d[0]), "+f"(d[1]), "+f"(d[2]), "+f"(d[3]), "+f"(d[4]), "+f"(d[5]), "+f"(d[6]), "+f"(d[7]), "+f"(d[8]), "+f"(d[9]), "+f"(d[10]), "+f"(d[11]), "+f"(d[12]), "+f"(d[13]), "+f"(d[14]), "+f"(d[15])
        : "r"(a[0]), "r"(a[1]), "r"(a[2]), "r"(a[3]), "l"(db));
}
__device__ __forceinline__ void wgmma_ss_n32(float (&d)[16], uint64_t da, uint64_t db) {
    asm volatile("wgmma.mma_async.sync.aligned.m64n32k16.f32.bf16.bf16 {%0, %1, %2, %3, %4, %5, %6, %7, %8, %9, %10, %11, %12, %13, %14, %15}, %16, %17, 1, 1, 1, 0, 0;"
        : "+f"(d[0]), "+f"(d[1]), "+f"(d[2]), "+f"(d[3]), "+f"(d[4]), "+f"(d[5]), "+f"(d[6]), "+f"(d[7]), "+f"(d[8]), "+f"(d[9]), "+f"(d[10]), "+f"(d[11]), "+f"(d[12]), "+f"(d[13]), "+f"(d[14]), "+f"(d[15])
        : "l"(da), "l"(db));
}
__device__ __forceinline__ void wgmma_rs_n64(float (&d)[32], const uint32_t* a, uint64_t db) {
    asm volatile("wgmma.mma_async.sync.aligned.m64n64k16.f32.bf16.bf16 {%0, %1, %2, %3, %4, %5, %6, %7, %8, %9, %10, %11, %12, %13, %14, %15, %16, %17, %18, %19, %20, %21, %22, %23, %24, %25, %26, %27, %28, %29, %30, %31}, {%32, %33, %34, %35}, %36, 1, 1, 1, 0;"
        : "+f"(d[0]), "+f"(d[1]), "+f"(d[2]), "+f"(d[3]), "+f"(d[4]), "+f"(d[5]), "+f"(d[6]), "+f"(d[7]), "+f"(d[8]), "+f"(d[9]), "+f"(d[10]), "+f"(d[11]), "+f"(d[12]), "+f"(d[13]), "+f"(d[14]), "+f"(d[15]), "+f"(d[16]), "+f"(d[17]), "+f"(d[18]), "+f"(d[19]), "+f"(d[20]), "+f"(d[21]), "+f"(d[22]), "+f"(d[23]), "+f"(d[24]), "+f"(d[25]), "+f"(d[26]), "+f"(d[27]), "+f"(d[28]), "+f"(d[29]), "+f"(d[30]), "+f"(d[31])
        : "r"(a[0]), "r"(a[1]), "r"(a[2]), "r"(a[3]), "l"(db));
}
__device__ __forceinline__ void wgmma_ss_n64(float (&d)[32], uint64_t da, uint64_t db) {
    asm volatile("wgmma.mma_async.sync.aligned.m64n64k16.f32.bf16.bf16 {%0, %1, %2, %3, %4, %5, %6, %7, %8, %9, %10, %11, %12, %13, %14, %15, %16, %17, %18, %19, %20, %21, %22, %23, %24, %25, %26, %27, %28, %29, %30, %31}, %32, %33, 1, 1, 1, 0, 0;"
        : "+f"(d[0]), "+f"(d[1]), "+f"(d[2]), "+f"(d[3]), "+f"(d[4]), "+f"(d[5]), "+f"(d[6]), "+f"(d[7]), "+f"(d[8]), "+f"(d[9]), "+f"(d[10]), "+f"(d[11]), "+f"(d[12]), "+f"(d[13]), "+f"(d[14]), "+f"(d[15]), "+f"(d[16]), "+f"(d[17]), "+f"(d[18]), "+f"(d[19]), "+f"(d[20]), "+f"(d[21]), "+f"(d[22]), "+f"(d[23]), "+f"(d[24]), "+f"(d[25]), "+f"(d[26]), "+f"(d[27]), "+f"(d[28]), "+f"(d[29]), "+f"(d[30]), "+f"(d[31])
        : "l"(da), "l"(db));
}
__device__ __forceinline__ void wgmma_rs_n128(float (&d)[64], const uint32_t* a, uint64_t db) {
    asm volatile("wgmma.mma_async.sync.aligned.m64n128k16.f32.bf16.bf16 {%0, %1, %2, %3, %4, %5, %6, %7, %8, %9, %10, %11, %12, %13, %14, %15, %16, %17, %18, %19, %20, %21, %22, %23, %24, %25, %26, %27, %28, %29, %30, %31, %32, %33, %34, %35, %36, %37, %38, %39, %40, %41, %42, %43, %44, %45, %46, %47, %48, %49, %50, %51, %52, %53, %54, %55, %56, %57, %58, %59, %60, %61, %62, %63}, {%64, %65, %66, %67}, %68, 1, 1, 1, 0;"
        : "+f"(d[0]), "+f"(d[1]), "+f"(d[2]), "+f"(d[3]), "+f"(d[4]), "+f"(d[5]), "+f"(d[6]), "+f"(d[7]), "+f"(d[8]), "+f"(d[9]), "+f"(d[10]), "+f"(d[11]), "+f"(d[12]), "+f"(d[13]), "+f"(d[14]), "+f"(d[15]), "+f"(d[16]), "+f"(d[17]), "+f"(d[18]), "+f"(d[19]), "+f"(d[20]), "+f"(d[21]), "+f"(d[22]), "+f"(d[23]), "+f"(d[24]), "+f"(d[25]), "+f"(d[26]), "+f"(d[27]), "+f"(d[28]), "+f"(d[29]), "+f"(d[30]), "+f"(d[31]), "+f"(d[32]), "+f"(d[33]), "+f"(d[34]), "+f"(d[35]), "+f"(d[36]), "+f"(d[37]), "+f"(d[38]), "+f"(d[39]), "+f"(d[40]), "+f"(d[41]), "+f"(d[42]), "+f"(d[43]), "+f"(d[44]), "+f"(d[45]), "+f"(d[46]), "+f"(d[47]), "+f"(d[48]), "+f"(d[49]), "+f"(d[50]), "+f"(d[51]), "+f"(d[52]), "+f"(d[53]), "+f"(d[54]), "+f"(d[55]), "+f"(d[56]), "+f"(d[57]), "+f"(d[58]), "+f"(d[59]), "+f"(d[60]), "+f"(d[61]), "+f"(d[62]), "+f"(d[63])
        : "r"(a[0]), "r"(a[1]), "r"(a[2]), "r"(a[3]), "l"(db));
}
__device__ __forceinline__ void wgmma_ss_n128(float (&d)[64], uint64_t da, uint64_t db) {
    asm volatile("wgmma.mma_async.sync.aligned.m64n128k16.f32.bf16.bf16 {%0, %1, %2, %3, %4, %5, %6, %7, %8, %9, %10, %11, %12, %13, %14, %15, %16, %17, %18, %19, %20, %21, %22, %23, %24, %25, %26, %27, %28, %29, %30, %31, %32, %33, %34, %35, %36, %37, %38, %39, %40, %41, %42, %43, %44, %45, %46, %47, %48, %49, %50, %51, %52, %53, %54, %55, %56, %57, %58, %59, %60, %61, %62, %63}, %64, %65, 1, 1, 1, 0, 0;"
        : "+f"(d[0]), "+f"(d[1]), "+f"(d[2]), "+f"(d[3]), "+f"(d[4]), "+f"(d[5]), "+f"(d[6]), "+f"(d[7]), "+f"(d[8]), "+f"(d[9]), "+f"(d[10]), "+f"(d[11]), "+f"(d[12]), "+f"(d[13]), "+f"(d[14]), "+f"(d[15]), "+f"(d[16]), "+f"(d[17]), "+f"(d[18]), "+f"(d[19]), "+f"(d[20]), "+f"(d[21]), "+f"(d[22]), "+f"(d[23]), "+f"(d[24]), "+f"(d[25]), "+f"(d[26]), "+f"(d[27]), "+f"(d[28]), "+f"(d[29]), "+f"(d[30]), "+f"(d[31]), "+f"(d[32]), "+f"(d[33]), "+f"(d[34]), "+f"(d[35]), "+f"(d[36]), "+f"(d[37]), "+f"(d[38]), "+f"(d[39]), "+f"(d[40]), "+f"(d[41]), "+f"(d[42]), "+f"(d[43]), "+f"(d[44]), "+f"(d[45]), "+f"(d[46]), "+f"(d[47]), "+f"(d[48]), "+f"(d[49]), "+f"(d[50]), "+f"(d[51]), "+f"(d[52]), "+f"(d[53]), "+f"(d[54]), "+f"(d[55]), "+f"(d[56]), "+f"(d[57]), "+f"(d[58]), "+f"(d[59]), "+f"(d[60]), "+f"(d[61]), "+f"(d[62]), "+f"(d[63])
        : "l"(da), "l"(db));
}

__device__ __forceinline__ uint32_t pack_bf16(float lo, float hi) {
    uint32_t r; asm("cvt.rn.bf16x2.f32 %0, %1, %2;" : "=r"(r) : "f"(hi), "f"(lo)); return r;
}
__device__ __forceinline__ uint32_t lds32(uint32_t a) { uint32_t v; asm volatile("ld.shared.b32 %0, [%1];" : "=r"(v) : "r"(a)); return v; }
__device__ __forceinline__ void sts32(uint32_t a, uint32_t v) { asm volatile("st.shared.b32 [%0], %1;" ::"r"(a), "r"(v) : "memory"); }
__device__ __forceinline__ void sts128(uint32_t a, uint4 v) { asm volatile("st.shared.v4.b32 [%0], {%1,%2,%3,%4};" ::"r"(a), "r"(v.x), "r"(v.y), "r"(v.z), "r"(v.w) : "memory"); }
__device__ __forceinline__ void stg128(void* p, uint4 v) { asm volatile("st.global.v4.b32 [%0], {%1,%2,%3,%4};" ::"l"(p), "r"(v.x), "r"(v.y), "r"(v.z), "r"(v.w) : "memory"); }
__device__ __forceinline__ void cp16(uint32_t dst, const void* src) { asm volatile("cp.async.cg.shared.global [%0], [%1], 16;" ::"r"(dst), "l"(src) : "memory"); }
__device__ __forceinline__ void cp_commit() { asm volatile("cp.async.commit_group;" ::: "memory"); }
template <int N> __device__ __forceinline__ void cp_wait() { asm volatile("cp.async.wait_group %0;" ::"n"(N) : "memory"); }
__device__ __forceinline__ uint4 dequant8(uint32_t raw, uint32_t lut_a) {
    uint32_t v[8];
#pragma unroll
    for (int i = 0; i < 8; i++) v[i] = lds32(raw + i * 128);
#pragma unroll
    for (int i = 0; i < 8; i++) v[i] = lds32(lut_a + v[i] * 128);
    uint4 o;
    o.x = __byte_perm(v[0], v[1], 0x5410); o.y = __byte_perm(v[2], v[3], 0x5410);
    o.z = __byte_perm(v[4], v[5], 0x5410); o.w = __byte_perm(v[6], v[7], 0x5410);
    return o;
}
__device__ __forceinline__ uint32_t prmt(uint32_t a, uint32_t b, uint32_t c) { uint32_t r; asm("prmt.b32 %0, %1, %2, %3;" : "=r"(r) : "r"(a), "r"(b), "r"(c)); return r; }
__device__ __forceinline__ uint4 lookup8_reg(const uint32_t* c, const uint32_t (&T)[8], uint32_t two31) {
    uint32_t o[4];
#pragma unroll
    for (int h = 0; h < 2; h++) {
        const uint32_t sel = c[4 * h] + c[4 * h + 1] * 16 + c[4 * h + 2] * 256 + c[4 * h + 3] * 4096;
        const uint32_t s7 = sel & 0x7777u;
        uint32_t m;
        asm("lop3.b32 %0, %1, %2, 0x3210, 0xEA;" : "=r"(m) : "r"(__umulhi(sel, two31)), "r"(0x4444u));
        const uint32_t lo = prmt(prmt(T[0], T[1], s7), prmt(T[2], T[3], s7), m);
        const uint32_t hi = prmt(prmt(T[4], T[5], s7), prmt(T[6], T[7], s7), m);
        o[2 * h] = prmt(lo, hi, 0x5140u); o[2 * h + 1] = prmt(lo, hi, 0x7362u);
    }
    return make_uint4(o[0], o[1], o[2], o[3]);
}
template <int OFF, int G0, int G1, int N>
__device__ __forceinline__ void store_tile(const float (&acc)[N], __nv_bfloat16* o) {
#pragma unroll
    for (int G = G0; G < G1; G++) {
        uint4 v;
        v.x = pack_bf16(acc[G * 16 + 0], acc[G * 16 + 1]); v.y = pack_bf16(acc[G * 16 + 4], acc[G * 16 + 5]);
        v.z = pack_bf16(acc[G * 16 + 8], acc[G * 16 + 9]); v.w = pack_bf16(acc[G * 16 + 12], acc[G * 16 + 13]);
        stg128(o + OFF + G * 32, v);
        v.x = pack_bf16(acc[G * 16 + 2], acc[G * 16 + 3]); v.y = pack_bf16(acc[G * 16 + 6], acc[G * 16 + 7]);
        v.z = pack_bf16(acc[G * 16 + 10], acc[G * 16 + 11]); v.w = pack_bf16(acc[G * 16 + 14], acc[G * 16 + 15]);
        stg128(o + OFF + 8 * F_ + G * 32, v);
    }
}
template <int OFF, int N>
__device__ __forceinline__ void store_half(const float (&acc)[N], __nv_bfloat16* o, int H, int on = 1) {
    const int b = (H >> 1) * 16 + (H & 1) * 2;
    uint4 v;
    v.x = pack_bf16(acc[b + 0], acc[b + 1]); v.y = pack_bf16(acc[b + 4], acc[b + 5]);
    v.z = pack_bf16(acc[b + 8], acc[b + 9]); v.w = pack_bf16(acc[b + 12], acc[b + 13]);
    asm volatile("{\n.reg .pred p;\nsetp.ne.b32 p, %5, 0;\n@p st.global.v4.b32 [%0], {%1,%2,%3,%4};\n}"
                 ::"l"(o + OFF + (H & 1) * 8 * F_ + (H >> 1) * 32), "r"(v.x), "r"(v.y), "r"(v.z), "r"(v.w), "r"(on) : "memory");
}
template <int N>
__device__ __forceinline__ void pack_half(const float (&acc)[N], int H, uint32_t* r) {
    const int b = (H >> 1) * 16 + (H & 1) * 2;
#pragma unroll
    for (int i = 0; i < 4; i++) asm volatile("cvt.rn.bf16x2.f32 %0, %1, %2;" : "=r"(r[i]) : "f"(acc[b + 4 * i + 1]), "f"(acc[b + 4 * i]));
}
__device__ __forceinline__ void store_packed(__nv_bfloat16* o, int H, const uint32_t* r, int on) {
    asm volatile("{\n.reg .pred p;\nsetp.ne.b32 p, %5, 0;\n@p st.global.v4.b32 [%0], {%1,%2,%3,%4};\n}"
                 ::"l"(o + (H & 1) * 8 * F_ + (H >> 1) * 32), "r"(r[0]), "r"(r[1]), "r"(r[2]), "r"(r[3]), "r"(on) : "memory");
}
constexpr int NROUNDS = 8;
constexpr unsigned long long R_FIRST = 0xFDB97543ull, R_BATCH = 0x60050400ull, R_DOUBLE = 0x7C;
constexpr unsigned long long W_FLAG = 0x600504000ull;
constexpr unsigned L1_MASK = W4L2 ? 0x2A : 0x2E, L2_MASK = W4L2 ? 0x1EA : 0x1E8; constexpr int W12_AT = 8;
constexpr int NFAST = NF;
__device__ __forceinline__ int round_first(int r) { return (int)(R_FIRST >> (4 * r)) & 15; }
__device__ __forceinline__ int round_batch(int r) { return (int)(R_BATCH >> (4 * r)) & 15; }

#define TSK(w, i)
#define TSF(i)
#define TSP(i)
#define TSQ(i)
#define PW 0
#define TS9(i)
#define TS8(i)
#define TSW(w, i)

template <bool HARD>
__global__ void __launch_bounds__(256, 1)
fused_kernel(const int* __restrict__ qw, const unsigned short* __restrict__ lut, __nv_bfloat16* __restrict__ out,
             uint4* __restrict__ wscr, unsigned* __restrict__ flags, const uint32_t two31,
             const __grid_constant__ CUtensorMap tmq, const __grid_constant__ CUtensorMap tmx64, const __grid_constant__ CUtensorMap tmx
) {
    extern __shared__ uint8_t smem_raw[];
    const uint32_t sbase = HARD ? 1024u : (smem_u32(smem_raw) + 1023) & ~1023u;
    const uint32_t bars = sbase + OFF_BAR;
    const int tid = threadIdx.x, lane = tid & 31;
    const int mt = blockIdx.x & 7, g = blockIdx.x >> 3;
    unsigned clk0; asm volatile("mov.u32 %0, %%clock;" : "=r"(clk0));
    constexpr int SLAB_BYTES = 16 * BN * 4, OFF_SLAB0 = OFF_W + 2 * W_BYTES, OFF_SLAB2 = OFF_X + 2 * X_BYTES;
    const int warp = __shfl_sync(0xffffffff, tid >> 5, 0);
    if (tid >= 224) {
        asm volatile("{\n.reg .pred p;\nelect.sync _|p, 0xffffffff;\n"
                     "@p mbarrier.init.shared::cta.b64 [%0], 1;\n"
                     "@p fence.mbarrier_init.release.cluster;\n"
                     "@p mbarrier.arrive.expect_tx.shared::cta.b64 _, [%0], %1;\n"
                     "@p cp.async.bulk.tensor.2d.shared::cluster.global.mbarrier::complete_tx::bytes [%3], [%2, {%4, 0}], [%0];\n}"
                     ::"r"(bars + 8 * B_SLAB), "n"(SLAB_BYTES), "l"(&tmq), "r"(sbase + OFF_SLAB0), "r"(g * BN) : "memory");
    } else {
        const unsigned short* lp = ptr_add(lut, ((lane >> 2) * F_ + g * BN + (tid & ~31) + (lane & 3) * 8) * 2);
        asm volatile("cp.async.cg.shared.global [%0], [%1], 16;\ncp.async.cg.shared.global [%0+512], [%1+57344], 16;\ncp.async.commit_group;"
                     ::"r"(sbase + OFF_STG + (tid >> 5) * 4096 + lane * 16), "l"(lp) : "memory");
    }
    const int sl = warp - 3;
    auto load_slab = [&]() {
        e_tma(bars + 8 * (B_SLAB + sl), &tmq, sbase + (sl < 2 ? OFF_SLAB0 : OFF_SLAB2 - 2 * SLAB_BYTES) + sl * SLAB_BYTES, g * BN, sl * 16);
    };
    if (warp >= 4 && warp < 7) {
        asm volatile("{\n.reg .pred p;\nelect.sync _|p, 0xffffffff;\n"
                     "@p mbarrier.init.shared::cta.b64 [%0], 1;\n"
                     "@p fence.mbarrier_init.release.cluster;\n"
                     "@p mbarrier.arrive.expect_tx.shared::cta.b64 _, [%0], %1;\n}"
                     ::"r"(bars + 8 * (B_SLAB + sl)), "n"(SLAB_BYTES) : "memory");
        if (sl < NOW) load_slab();
    } else if (warp < 2) {
        asm volatile("{\n.reg .pred p;\nelect.sync _|p, 0xffffffff;\n"
                     "@p mbarrier.init.shared::cta.b64 [%0], %1;\n"
                     "@p fence.mbarrier_init.release.cluster;\n}" ::"r"(bars + 8 * (warp ? B_LUT : B_FULL)), "r"(8 - warp) : "memory");
    }
    asm volatile("bar.sync 1, 256;" ::: "memory");
    TSQ(0);
    const int wg = warp >> 2;

    const int fl = 8 * ((lane & 7) >> 1) + 2 * (lane >> 3) + (lane & 1);
    const uint32_t lut_a = sbase + OFF_LUT + warp * 2048 + lane * 4;
    const uint32_t stg = sbase + OFF_STG + warp * 4096;
    unsigned* myflags = flags + g * 32;
    const uint4* wgrp = wscr + (size_t)g * 128 * BN;
    unsigned target = 0;

    auto issue_x = [&](int s, int slot) {
        e_tma(bars + 8 * (B_FULL + s), &tmx, sbase + OFF_X + slot * X_BYTES, s * BK, mt * BM);
    };
    auto pf_x = [&](int s, int row0) { e_prefetch2d(&tmx64, s * BK, row0); };
    auto issue_xv = [&](int v, int w, uint32_t bar) {
        const uint32_t dst = sbase + OFF_X + (v & 1) * X_BYTES + w * 16384;
        const int k0 = (12 + 2 * (v & 1)) * BK, r0 = mt * BM + w * 128 + ((v >> 1) & 1) * 64;
        e_tma(bar, &tmx64, dst, k0, r0);
        e_tma(bar, &tmx64, dst + 8192, k0 + BK, r0);
    };
    auto issue_w = [&](int s, int slot, int bar) {
        e_bulk(bars + 8 * bar, W_BYTES, sbase + OFF_W + slot * W_BYTES, wgrp + s * 8 * BN);
    };
    auto load_raw = [&](int t) {
        if (t < 16) {
            const int* src = ptr_add(qw, (uint32_t)(((t * BK + mt * 8 + (lane >> 3)) * F_ + g * BN + warp * 32 + (lane & 7) * 4) * 4));
            asm volatile("cp.async.cg.shared.global [%0], [%1], 16;\ncp.async.cg.shared.global [%0+512], [%1+57344], 16;"
                         ::"r"(stg + (t & 3) * 1024 + lane * 16), "l"(src) : "memory");
        }
        cp_commit();
    };
    auto load_blk = [&](int t, int c) {
        const int* src = ptr_add(qw, (uint32_t)(((t * BK + mt * 8 + (lane >> 3)) * F_ + g * BN + c * 32 + (lane & 7) * 4) * 4));
        asm volatile("cp.async.cg.shared.global [%0], [%1], 16;\ncp.async.cg.shared.global [%0+512], [%1+57344], 16;"
                     ::"r"(sbase + OFF_STG + c * 4096 + t * 1024 + lane * 16), "l"(src) : "memory");
    };
    auto foreign = [&](int t) {
        const int c = warp ^ 4;
        stg128(ptr_add(wscr, (uint32_t)(((g * 128 + t * 8 + mt) * BN + c * 32 + lane) * 16)),
               dequant8(sbase + OFF_STG + c * 4096 + t * 1024 + fl * 4, sbase + OFF_LUT + c * 2048 + lane * 4));
        TSW(4, 5);
    };
    auto my_unit = [&](int t) { return ptr_add(wscr, (uint32_t)(((g * 128 + t * 8 + mt) * BN + warp * 32 + lane) * 16)); };
    auto coop = [&](int t) {
        cp_wait<LA - 1>();
        __syncwarp();
        load_raw(t + LA);
        stg128(my_unit(t), dequant8(stg + (t & 3) * 1024 + fl * 4, lut_a));

    };
    auto coop2 = [&](int t) {
        cp_wait<0>();
        __syncwarp();
        if (t < 14) {
            const int* src = ptr_add(qw, (uint32_t)((((t + 2) * BK + mt * 8 + (lane >> 3)) * F_ + g * BN + warp * 32 + (lane & 7) * 4) * 4));
            asm volatile("cp.async.cg.shared.global [%0], [%1], 16;\ncp.async.cg.shared.global [%0+512], [%1+57344], 16;"
                         ::"r"(stg + ((t + 2) & 3) * 1024 + lane * 16), "l"(src) : "memory");
            if (t < 13) asm volatile("cp.async.cg.shared.global [%0], [%1+917504], 16;\ncp.async.cg.shared.global [%0+512], [%1+974848], 16;"
                                     ::"r"(stg + ((t + 3) & 3) * 1024 + lane * 16), "l"(src) : "memory");
            cp_commit();
        }
        uint32_t v[16];
        const uint32_t r0 = stg + (t & 3) * 1024 + fl * 4, r1 = stg + ((t + 1) & 3) * 1024 + fl * 4;
#pragma unroll
        for (int i = 0; i < 8; i++) v[i] = lds32(r0 + i * 128);
#pragma unroll
        for (int i = 0; i < 8; i++) v[8 + i] = lds32(r1 + i * 128);
#pragma unroll
        for (int i = 0; i < 16; i++) v[i] = lds32(lut_a + v[i] * 128);
        uint4* dst = my_unit(t);
        stg128(dst, make_uint4(prmt(v[0], v[1], 0x5410), prmt(v[2], v[3], 0x5410), prmt(v[4], v[5], 0x5410), prmt(v[6], v[7], 0x5410)));
        if (t < 15) stg128(dst + 8 * BN, make_uint4(prmt(v[8], v[9], 0x5410), prmt(v[10], v[11], 0x5410), prmt(v[12], v[13], 0x5410), prmt(v[14], v[15], 0x5410)));
    };
    auto pace = [&](unsigned t) { unsigned c; do { asm volatile("mov.u32 %0, %%clock;" : "=r"(c)); } while (c - clk0 < t); };
    if (warp == 7) {
        TSW(7, 2); TSQ(1);
        if (lane == 0) {
            asm volatile("prefetch.tensormap [%0];" ::"l"(&tmx) : "memory");
            asm volatile("prefetch.tensormap [%0];" ::"l"(&tmx64) : "memory");
        }
        __syncwarp();
        TSW(7, 13); TSQ(3);
        auto xh = [&](int s, int w, uint32_t bar) {
            e_tma(bar, &tmx64, sbase + OFF_X + s * X_BYTES + w * 16384, s * BK, mt * BM + w * 128);
            e_tma(bar, &tmx64, sbase + OFF_X + s * X_BYTES + w * 16384 + 8192, s * BK, mt * BM + w * 128 + 64);
        };
        pace(PX0);
        if (XS & 1) { e_expect(bars + 8 * B_FULL, X_BYTES / 2); xh(0, 0, bars + 8 * B_FULL); }
        else { e_expect(bars + 8 * B_FULL, X_BYTES); issue_x(0, 0); }
        TSQ(4);
        if (R1MODE == 4) {
            pace(PR1);
#pragma unroll
            for (int c = 0; c < 4; c++) load_blk(1, c);
            cp_commit();
        }
        target = ld_flag(myflags + 6);
        TSW(7, 1);
        pace(PR2);
        load_blk(2, 3);
        cp_commit();
        mbar_wait(bars + 8 * B_LUT);
        if (R1MODE == 4) {
            uint32_t c[32];
            cp_wait<1>();
            __syncwarp();
#pragma unroll
            for (int i = 0; i < 32; i++) c[i] = lds32(sbase + OFF_STG + (i >> 3) * 4096 + 1024 + (i & 7) * 128 + fl * 4);
#pragma unroll
            for (int i = 0; i < 32; i++) c[i] = lds32(sbase + OFF_LUT + (i >> 3) * 2048 + lane * 4 + c[i] * 128);
            uint4* dst = ptr_add(wscr, (uint32_t)(((g * 128 + 8 + mt) * BN + lane) * 16));
#pragma unroll
            for (int b = 0; b < 4; b++)
                stg128(dst + b * 32, make_uint4(prmt(c[8 * b], c[8 * b + 1], 0x5410), prmt(c[8 * b + 2], c[8 * b + 3], 0x5410),
                                                prmt(c[8 * b + 4], c[8 * b + 5], 0x5410), prmt(c[8 * b + 6], c[8 * b + 7], 0x5410)));
            TSW(7, 14);
        }
        if (XS & 1) { pace(PX0B); e_expect(bars + 8 * B_L, X_BYTES / 2); xh(0, 1, bars + 8 * B_L); }
        target = (target | 7) + 1;
        if (PFX > 100) { pace(PFX); pf_x(PFXB + (g >> 2), mt * BM + (g & 3) * 64); }
        if (PX1 < 100000) { pace(PX1); issue_x(1, 1); }
        if (F2POS == 0) { cp_wait<0>(); __syncwarp(); foreign(2); }
        mbar_wait(bars + 8 * B_FULL);
        if (PX1 == 100000) { if (XS & 2) xh(1, 0, bars + 8 * (B_FULL + 1)); else issue_x(1, 1); }
        if (PFX == 1) pf_x(PFXB + (g >> 2), mt * BM + (g & 3) * 64);
        if (F2POS == 1) { cp_wait<0>(); __syncwarp(); foreign(2); }
        if (W1BY == 7) {
            if (W1D) { unsigned c, c0; asm volatile("mov.u32 %0, %%clock;" : "=r"(c0)); do { asm volatile("mov.u32 %0, %%clock;" : "=r"(c)); } while (c - c0 < W1D); }
            e_bulk_p(1, bars + 8 * (B_FULL + 1), W_BYTES, sbase + OFF_W + W_BYTES, wgrp + 8 * BN);
            TSW(7, 4);
        }
        if (PX1 == 100001) issue_x(1, 1);
        if (F2POS == 2) { cp_wait<0>(); __syncwarp(); foreign(2); }
        if (PFX == 2) pf_x(PFXB + (g >> 2), mt * BM + (g & 3) * 64);
        TSW(7, 3);
    } else {
        if (wg == 1 && sl >= NOW) { pace(PSBASE + sl * PSTEP); load_slab(); }
        auto init6 = [&](auto wc) {
            constexpr int w = decltype(wc)::value;
#pragma unroll
            for (int i = 0; i < 6; i++) { constexpr int b0 = 1 + w * 6; if (b0 + i < B_SLAB) mbar_init(bars + 8 * (b0 + i), b0 + i <= B_L + 3 ? 1 : 7); }
#pragma unroll
            for (int i = 0; i < 6; i++) {
                constexpr int b0 = 1 + w * 6;
                if (b0 + i < B_XV) asm volatile("mbarrier.arrive.expect_tx.shared::cta.b64 _, [%0], %1;" ::"r"(bars + 8 * (b0 + i)), "n"(X_BYTES + W_BYTES) : "memory");
            }
        };
        auto init_bars = [&]() {
            if (lane == 0) {
#pragma unroll
                for (int i = 0; i < 6; i++) {
                    const int b = 1 + warp * 6 + i;
                    if (b < B_SLAB) mbar_init(bars + 8 * b, b <= B_L + 3 ? 1 : 7);
                    if (b < B_XV) asm volatile("mbarrier.arrive.expect_tx.shared::cta.b64 _, [%0], %1;" ::"r"(bars + 8 * b), "r"(((XS & 2) && b == 1 ? X_BYTES / 2 : X_BYTES) + W_BYTES) : "memory");
                }
                asm volatile("fence.mbarrier_init.release.cluster;" ::: "memory");
            }
            __syncwarp();
        };
        if (R1PRE) { pace(PR1); load_blk(1, warp); cp_commit(); }
        init_bars();
        if (!R1PRE) { pace(PR1); load_blk(1, warp); cp_commit(); }
        TSW(0, 15);
        uint32_t lv[16], v[32], T[8];
        cp_wait<1>();
        __syncwarp();
#pragma unroll
        for (int i = 0; i < 16; i++) asm volatile("ld.shared.u16 %0, [%1];" : "=r"(lv[i]) : "r"(stg + i * 64 + fl * 2));
#pragma unroll
        for (int i = 0; i < 16; i++) lv[i] = lv[i] ? lv[i] : 0x8000u;
#pragma unroll
        for (int i = 0; i < 4; i++) {
            const uint32_t p01 = prmt(lv[4 * i], lv[4 * i + 1], 0x5140u), p23 = prmt(lv[4 * i + 2], lv[4 * i + 3], 0x5140u);
            T[i] = prmt(p01, p23, 0x5410u); T[4 + i] = prmt(p01, p23, 0x7632u);
        }
        TSW(0, 7);
#pragma unroll
        for (int i = 0; i < 16; i++) sts32(lut_a + i * 128, lv[i]);
        __syncwarp();
        e_arrive(bars + 8 * B_LUT);
        auto more_raw = [&](int j) {
            if (R2AT == j && wg == 1) { load_blk(2, warp); load_blk(2, warp - 4); cp_commit(); }
            if (R3AT == j && wg == 0) load_raw(3);
            if (R3W1 == j && wg == 1) load_raw(3);
        };
        auto own_task = [&](int t) {
            __syncwarp();
            uint32_t c[8];
#pragma unroll
            for (int i = 0; i < 8; i++) c[i] = lds32(stg + t * 1024 + fl * 4 + i * 128);
            uint4 o = lookup8_reg(c, T, two31);
            stg128(my_unit(t), o);
            if (t == 1) { TSW(4, 6); if (R1MODE != 4) TSW(0, 14); }
        };
        auto raw1_task = [&]() {
            if (wg == 1) cp_wait<(R2AT < 4) + (R3W1 < 4)>(); else cp_wait<(R3AT < 4)>();
            own_task(1);
        };
        auto piece_ld = [&](int j) {
            TSP(j * 8);
            mbar_wait(bars + 8 * (B_SLAB + j));
            TSP(j * 8 + 1);
#pragma unroll
            for (int i = 0; i < 16; i++) v[(j & 1) * 16 + i] = lds32(sbase + (j < 2 ? OFF_SLAB0 : OFF_SLAB2) + (j & 1) * SLAB_BYTES + i * (BN * 4) + (warp * 32 + fl) * 4);
            more_raw(j);
        };
        auto piece_st = [&](int j) {
            const uint32_t dst = sbase + OFF_W + j * 2 * CHUNK_BYTES + (warp * 32 + lane) * 16;
            sts128(dst, lookup8_reg(v + (j & 1) * 16, T, two31));
            sts128(dst + CHUNK_BYTES, lookup8_reg(v + (j & 1) * 16 + 8, T, two31));
            TSP(j * 8 + 2);
            TSW(PW, 8 + j);
        };
        if (R2AT < 0 && wg == 1) { pace(PR2); more_raw(R2AT); }
        piece_ld(0);
        if (PIPE & 1) piece_ld(1);
        piece_st(0);
        if (!(PIPE & 1)) piece_ld(1);
        if (PIPE & 2) piece_ld(2);
        piece_st(1);
        if (!(PIPE & 2)) piece_ld(2);
        if (PIPE & 4) piece_ld(3);
        piece_st(2);
        if (!(PIPE & 4)) piece_ld(3);
        if (R1MODE == 2 || (R1MODE == 3 && wg == 0)) raw1_task();
        piece_st(3);
        asm volatile("fence.proxy.async.shared::cta;" ::: "memory");
        TSP(27);
        __syncwarp();
        e_arrive(bars + 8 * B_FULL);
        if (R1MODE == 1 || (wg == 1 && R1MODE >= 3)) raw1_task();
        more_raw(4);
        if (wg == 1) {
            cp_wait<(R3W1 < 5)>();
            own_task(2);
            if (R34AT == 0) { if (R3W1 == 5) load_raw(3); load_raw(4); }
            mbar_wait(bars + 8 * B_LUT);
            foreign(2);
            if (R34AT == 1) { if (R3W1 == 5) load_raw(3); load_raw(4); }
        }
        TSW(4, 12);
    }

    float acc0[112], acc1[112];
    const uint64_t descA_hi = ((uint64_t)1 << 62) | ((uint64_t)(1024 >> 4) << 32) | ((uint64_t)1 << 16);
    const uint64_t descB_hi = ((uint64_t)(128 >> 4) << 32) | ((uint64_t)(CHUNK_BYTES >> 4) << 16);
    const uint32_t a16 = ((sbase & 0x3FFFF) >> 4) + wg * 1024 + (uint32_t)descA_hi, b16w = (((sbase + OFF_W) & 0x3FFFF) >> 4) + (uint32_t)descB_hi;
    auto dscA = [&](uint32_t lo) { return (descA_hi & 0xFFFFFFFF00000000ull) | lo; };
    auto dscB = [&](uint32_t lo) { return (descB_hi & 0xFFFFFFFF00000000ull) | lo; };
    uint32_t xo = 0, wo = 0, wo_prev = 2 * W_BYTES;
    const uint4* wnext = wgrp + 2 * 8 * BN;
    auto validate = [&](int t, uint32_t wofs) {
        constexpr int NV = VSPLIT == 1 ? 7 : 14;
        const uint32_t u = VSPLIT == 1 ? tid + wg * (W_BYTES / 32 - 128) : tid & 127;
        const uint32_t a = sbase + OFF_W + wofs + u * 16;
        for (int n = 0; n < 2000000; n++) {
            uint32_t m = 0xffffffffu;
#pragma unroll
            for (int i = 0; i < 7; i++) m = min(m, lds32(a + u * 16 + (lane >> 2) * 4 + i * 4096));
            if (__all_sync(0xffffffff, m != 0)) break;
            const uint4* src = ptr_add(wgrp, (uint32_t)((t * 8 * BN + (u & ~31) * 2 + lane) * 16));
#pragma unroll 1
            for (int i = 0; i < 14; i++) cp16(sbase + OFF_W + wofs + ((u & ~31) * 2 + lane + (i >> 1) * 256 + (i & 1) * 32) * 16, src + (i >> 1) * 256 + (i & 1) * 32);
            cp_commit();
            cp_wait<0>();
            asm volatile("fence.proxy.async.shared::cta;" ::: "memory");
            __syncwarp();
        }
    };
    auto batch = [&](int s, bool val) {
        if (val && s == 0) TSP(28);
        mbar_wait(bars + 8 * (B_FULL + s));
        if (val && s == 0) TSP(29);
        if (wg == 1 && s < 2 && ((XS >> s) & 1)) mbar_wait(bars + 8 * (B_L + 3 * s));
        if (val && VSPLIT != 2 && wg == 0 && (unsigned)(s - 1) < NFAST) validate(s, wo);
        if (s + wg > 0) asm volatile("bar.sync %0, 256;" ::"r"(2 + wg) : "memory");
        TSW(0, 16 + s); TSW(4, 48 + s); TS8(16 + s);
        const uint32_t al = a16 + (xo >> 4), bl = b16w + (wo >> 4);
        wgmma_fence();
#pragma unroll
        for (int kk = 0; kk < 4; kk++) {
            const uint64_t db = dscB(bl + kk * (2 * CHUNK_BYTES >> 4));
            wgmma_m64n224k16(acc0, dscA(al + kk * 2), db, (s | kk) != 0);
            wgmma_m64n224k16(acc1, dscA(al + kk * 2 + (8192 >> 4)), db, (s | kk) != 0);
        }
        wgmma_commit();
        if (val && VSPLIT && wg == 1 && s < NFAST) { mbar_wait(bars + 8 * (B_FULL + s + 1)); validate(s + 1, 3 * W_BYTES - wo - wo_prev); }
        asm volatile("bar.arrive %0, 256;" ::"r"(3 - wg) : "memory");
        TSW(0, 32 + s); TSW(4, 64 + s);
    };
    auto advance = [&]() {
        wo_prev = wo;
        xo = xo == 2 * X_BYTES ? 0 : xo + X_BYTES;
        wo = wo == 2 * W_BYTES ? 0 : wo + W_BYTES;
        wnext += 8 * BN;
    };
    if (PEEL) batch(0, false);
#pragma unroll 1
    for (int s = 0; s < 9; s++) {
        if (!PEEL) batch(s, true);
        const uint32_t bs = bars + 8 * s;
        if (warp == 7) {
            const int fb = (int)(W_FLAG >> (4 * s)) & 15;
            unsigned* fp = ptr_add(myflags, fb * 4);
            unsigned fv = target;
            const int pb = round_batch(s);
            const uint32_t l1 = (L1_MASK >> s) & 1, l2 = (L2_MASK >> s) & 1;
            if (fb) fv = ld_flag(fp);
            else e_bulk_p(l1 && (L1PRE || !pb), bs + 8 * (B_FULL + 2), W_BYTES, sbase + OFF_W + wo_prev, wnext);
            if (s == 0) {
                if (XS & 2) {
                    e_expect(bars + 8 * (B_L + 3), X_BYTES / 2);
                    e_tma(bars + 8 * (B_L + 3), &tmx64, sbase + OFF_X + X_BYTES + 16384, BK, mt * BM + 128);
                    e_tma(bars + 8 * (B_L + 3), &tmx64, sbase + OFF_X + X_BYTES + 16384 + 8192, BK, mt * BM + 192);
                }
                if (X2POS == 0) issue_x(2, 2);
                if (PFX == 3) pf_x(PFXB + (g >> 2), mt * BM + (g & 3) * 64);
                if (W2POS == 0) {
                    if (W2D) { unsigned c, c0; asm volatile("mov.u32 %0, %%clock;" : "=r"(c0)); do { asm volatile("mov.u32 %0, %%clock;" : "=r"(c)); } while (c - c0 < W2D); }
                    e_bulk_p(1, bs + 8 * (B_FULL + 2), W_BYTES, sbase + OFF_W + wo_prev, wnext);
                }
            }
            TSW(7, 112 + s);
            if (s == 0 && X2POS == 1) issue_x(2, 2);
            if (pb) {
                mbar_wait(bars + 8 * (B_DQ + pb));
                mbar_wait(bs + 8 * B_EMPTY);
                e_publish(ptr_add(myflags, pb * 4));
                if (!L1PRE) e_bulk_p(l1, bs + 8 * (B_FULL + 2), W_BYTES, sbase + OFF_W + wo_prev, wnext);
            } else {
                if (fb) {
                    finish_poll(fp, fv, target);
                    e_bulk_p(l1, bs + 8 * (B_FULL + 2), W_BYTES, sbase + OFF_W + wo_prev, wnext);
                }
                mbar_wait(bs + 8 * B_EMPTY);
                if (s == W12_AT) {
                    issue_w(12, 3, B_WF);
                    e_bulk(bars + 8 * (B_WF + 3), W_BYTES / 2, sbase + OFF_LUT, wgrp + 15 * 8 * BN);
                }
            }
            wgmma_wait<0>();
            if (W2POS == 1) e_bulk_p(s == 0, bs + 8 * (B_FULL + 2), W_BYTES, sbase + OFF_W + wo_prev, wnext);
            e_bulk_p(l2, bs + 8 * (B_FULL + 3), W_BYTES, sbase + OFF_W + wo, wnext + 8 * BN);
            e_tma(bs + 8 * (B_FULL + 3), &tmx, sbase + OFF_X + xo, (s + 3) * BK, mt * BM);
            TSW(7, 96 + s);
        } else {
            if (s == 0) {
                if (wg == 0) {
                    if (R3AT > 4) load_raw(3);
                    if (R4W0 == 0) load_raw(4);
                    if (warp == W1BY) {
                        if (W1D) { unsigned c, c0; asm volatile("mov.u32 %0, %%clock;" : "=r"(c0)); do { asm volatile("mov.u32 %0, %%clock;" : "=r"(c)); } while (c - c0 < W1D); }
                        e_bulk_p(1, bars + 8 * (B_FULL + 1), W_BYTES, sbase + OFF_W + W_BYTES, wgrp + 8 * BN); TSW(3, 4);
                    }
                } else if (R34AT == 2) { if (R3W1 == 5) load_raw(3); load_raw(4); }
            }
            const int r = s + wg;
            if (R4W0 && r == 0) {
                cp_wait<0>();
                __syncwarp();
                stg128(my_unit(3), dequant8(stg + 3 * 1024 + fl * 4, lut_a));
                if (R4W0 == 2) mbar_wait(bars + 8 * (B_FULL + 1));
                load_raw(4); load_raw(5);
            } else if (wg == 0 && s < 2) coop(s + 3);
            else if (r < NROUNDS) { if (PAIR) coop2(2 * r + 1); else { coop(2 * r + 1); if (r < 7) coop(2 * r + 2); } }
            if (round_batch(r)) { __syncwarp(); e_arrive(bars + 8 * (B_DQ + round_batch(r))); }
            TSW(0, 80 + s);
            wgmma_wait<0>();
            if (warp == 3) e_arrive(bs + 8 * B_EMPTY);
            if (warp == 2 && (s & 3) == 1) pf_x(s + 4 + (g >> 2), mt * BM + (g & 3) * 64);
        }
        advance();
        if (PEEL) batch(s + 1, true);
    }
    auto rezero = [&]() {
        mbar_wait(bars + 8 * (B_FULL + 11));
#pragma unroll
        for (int t = 1; t <= NFAST; t++) stg128(my_unit(t), make_uint4(0, 0, 0, 0));
    };
    const int w4 = warp & 3;
    __nv_bfloat16* o = ptr_add(out, (uint32_t)(((mt * BM + wg * 128 + w4 * 16 + (lane >> 2)) * F_ + g * BN + (lane & 3) * 8) * 2));
    auto wofs = [](int st, int kk) -> uint32_t {
        return st < 15 ? OFF_W + (st == 11 ? 2 : st == 12 ? 3 : st - 13) * W_BYTES + kk * 2 * CHUNK_BYTES
                       : kk < 2 ? OFF_LUT + kk * 2 * CHUNK_BYTES : OFF_X + 2 * X_BYTES + (kk - 2) * 16384;
    };
    auto xofs = [](int st, int kk, int r) -> uint32_t {
        return (st == 11 ? 2 * X_BYTES + r * 8192 : ((st - 12) >> 1) * X_BYTES + (st & 1) * 8192) + kk * 32;
    };
    auto launder = [&]() { uint32_t b16 = (sbase & 0x3FFFF) >> 4; asm volatile("mov.u32 %0, %0;" : "+r"(b16)); return b16; };
    auto dA = [&](uint32_t b16, uint32_t ofs) { return (descA_hi & 0xFFFFFFFF00000000ull) | (uint64_t)(b16 + wg * 1024 + (ofs >> 4) + (uint32_t)descA_hi); };
    auto dB = [&](uint32_t b16, uint32_t ofs) { return (descB_hi & 0xFFFFFFFF00000000ull) | (uint64_t)(b16 + (ofs >> 4) + (uint32_t)descB_hi); };
    float p0[64], p1[32], p2[16];
    constexpr int PK0 = ASP < CSP ? ASP : CSP;
    uint32_t pk[(14 - PK0) * 4 + 1];
    auto split_acc1 = [&]() {
#pragma unroll
        for (int i = 0; i < 64; i++) asm volatile("add.f32 %0, %1, 0f00000000;" : "=f"(p0[i]) : "f"(acc1[i]));
#pragma unroll
        for (int i = 0; i < 32; i++) asm volatile("add.f32 %0, %1, 0f00000000;" : "=f"(p1[i]) : "f"(acc1[64 + i]));
#pragma unroll
        for (int i = 0; i < 16; i++) asm volatile("add.f32 %0, %1, 0f00000000;" : "=f"(p2[i]) : "f"(acc1[96 + i]));
    };
    {
        if (!PEEL) batch(9, false);
        if (warp == 7) {
            pf_x(13 + (g >> 2), mt * BM + (g & 3) * 64);
            mbar_wait(bars + 8 * (B_EMPTY + 9));
        } else if (ZPOS == 9) rezero();
        wgmma_wait<0>();
        if (warp == 3) e_arrive(bars + 8 * (B_EMPTY + 9));
        if (warp == 7) {
            issue_w(13, 0, B_WF + 1);
            e_expect(bars + 8 * B_XV, X_BYTES);
            issue_xv(12, 0, bars + 8 * B_XV); issue_xv(12, 1, bars + 8 * B_XV);
        }
        advance();
        batch(10, false);
        if (warp == 7) mbar_wait(bars + 8 * (B_EMPTY + 10)); else if (ZPOS == 10) rezero();
        wgmma_wait<0>();
        if (warp == 3) e_arrive(bars + 8 * (B_EMPTY + 10));
    }
    {
        mbar_wait(bars + 8 * (B_FULL + 11));
        asm volatile("bar.sync %0, 256;" ::"r"(2 + wg) : "memory");
        const uint32_t b16 = launder();
        wgmma_fence();
#pragma unroll
        for (int kk = 0; kk < 4; kk++) wgmma_m64n224k16(acc0, dA(b16, xofs(11, kk, 0)), dB(b16, wofs(11, kk)), 1);
        wgmma_commit();
        asm volatile("bar.arrive %0, 256;" ::"r"(3 - wg) : "memory");
        if (warp == 7) {
            issue_w(14, 1, B_WF + 2);
            e_expect(bars + 8 * (B_XV + 1), X_BYTES);
            issue_xv(13, 0, bars + 8 * (B_XV + 1)); issue_xv(13, 1, bars + 8 * (B_XV + 1));
            mbar_wait(bars + 8 * (B_EMPTY + 11));
        } else if (ZPOS == 11) rezero();
        if (!PLAG && FADDPOS == 0) split_acc1();
        wgmma_wait<0>();
        if (warp == 3) e_arrive(bars + 8 * (B_EMPTY + 11));
        if (warp == 7) {
            e_bulk(bars + 8 * (B_WF + 4), 2 * CHUNK_BYTES, sbase + wofs(15, 2), wgrp + (15 * 8 + 4) * BN);
            e_bulk(bars + 8 * (B_XV + 4), 2 * CHUNK_BYTES, sbase + wofs(15, 3), wgrp + (15 * 8 + 6) * BN);
        }
    }
    uint32_t af[80];
    const uint32_t lm = sbase + wg * 16384 + (w4 * 16 + (lane & 15)) * 128 + (((lane >> 4) ^ (lane & 7)) << 4);
    auto ldfrag = [&](int st) {
#pragma unroll
        for (int kk = 0; kk < 4; kk++) {
            uint32_t* r = af + ((st - 11) * 4 + kk) * 4;
            asm volatile("ldmatrix.sync.aligned.m8n8.x4.shared.b16 {%0,%1,%2,%3}, [%4];" : "=r"(r[0]), "=r"(r[1]), "=r"(r[2]), "=r"(r[3])
                         : "r"((lm ^ (kk << 5)) + xofs(st, 0, 1)) : "memory");
        }
    };
    {
        asm volatile("bar.sync %0, 256;" ::"r"(2 + wg) : "memory");
        TSK(0, 28); TSF(0);
        const uint32_t b16 = launder();
#pragma unroll
        for (int st = 12; st < 16; st++) {
            if (!(st & 1)) mbar_wait(bars + 8 * (B_XV + ((st - 12) >> 1)));
            mbar_wait(bars + 8 * (B_WF + st - 12));
            if (!(st & 1)) wgmma_fence();
#pragma unroll
            for (int kk = 0; kk < 4; kk++) {
                if (st == 15 && kk >= 2) mbar_wait(bars + 8 * (kk == 2 ? B_WF + 4 : B_XV + 4));
                wgmma_m64n224k16(acc0, dA(b16, xofs(st, kk, 0)), dB(b16, wofs(st, kk)), 1);
            }
            if (st & 1) wgmma_commit();
        }
        asm volatile("bar.arrive %0, 256;" ::"r"(3 - wg) : "memory");
        TSF(1);
        if (!PLAG && FADDPOS == 1) split_acc1();
        wgmma_wait<1>();
        if (w4 == 3) { e_expect(bars + 8 * (B_XV + 2 + wg), X_BYTES / 2); issue_xv(14, wg, bars + 8 * (B_XV + 2 + wg)); }
        wgmma_wait<0>();
        if (w4 == 3 && (X15AT < 0 || wg == 1)) { e_expect(bars + 8 * (B_X15 + wg), X_BYTES / 2); issue_xv(15, wg, bars + 8 * (B_X15 + wg)); }
        TSF(2); TS9(0);
        unsigned tb; asm volatile("mov.u32 %0, %%clock;" : "=r"(tb));
        auto pst = [&](unsigned t) { unsigned c; do { asm volatile("mov.u32 %0, %%clock;" : "=r"(c)); } while (c - tb < t); };
#pragma unroll
        for (int h = 0; h < PK0; h++) {
            if (PSTA && h >= PSF) pst((h - PSF + 1) * PSTA);
            store_half<0>(acc0, o, h);
            if (X15AT == h && warp == 3) { e_expect(bars + 8 * B_X15, X_BYTES / 2); issue_xv(15, 0, bars + 8 * B_X15); }
            if (L11 == h) ldfrag(11);
            if (L12 == h) { mbar_wait(bars + 8 * (B_XV + 2 + wg)); ldfrag(12); if (L13) ldfrag(13); }
        }
#pragma unroll
        for (int h = PK0; h < 14; h++) pack_half(acc0, h, pk + (h - PK0) * 4);
#pragma unroll
        for (int h = PK0; h < (ASP > CSP ? ASP : CSP); h++) { if (PSTA && wg == (ASP > CSP ? 0 : 1)) pst((h - PSF + 1) * PSTA); store_packed(o, h, pk + (h - PK0) * 4, ASP > CSP ? wg ^ 1 : wg); }
        TSF(3);
    }
    {
        if (L11 < 0) ldfrag(11);
        asm volatile("bar.sync %0, 256;" ::"r"(2 + wg) : "memory");
        TSF(4);
        const uint32_t b16 = launder();
#pragma unroll
        for (int st = 11; st < 16; st++) {
            wgmma_fence();
#pragma unroll
            for (int kk = 0; kk < 4; kk++) {
                const int i = (st - 11) * 4 + kk;
                wgmma_rs_n128(p0, af + i * 4, dB(b16, wofs(st, kk)));
                if (i == 0) TS9(1);
                constexpr int PD = L12 < 0 ? 1 : 2 + L13;
                if (kk == 0 && st + PD < 16) {
                    if (st == 11 && L12 < 0) mbar_wait(bars + 8 * (B_XV + 2 + wg));
                    if (st + PD == 14) mbar_wait(bars + 8 * (B_X15 + wg));
                    ldfrag(st + PD);
                }
                if (i % ISTEP == 0) {
                    const int h0 = ASP + i / ISTEP, h1 = CSP + i / ISTEP;
                    if (ASP == CSP) { if (h0 < 14) store_packed(o, h0, pk + (h0 - PK0) * 4, 1); }
                    else {
                        if (h0 < 14) store_packed(o, h0, pk + (h0 - PK0) * 4, wg ^ 1);
                        if (h1 < 14) store_packed(o, h1, pk + (h1 - PK0) * 4, wg);
                    }
                }
            }
        }
        wgmma_commit();
        asm volatile("bar.arrive %0, 256;" ::"r"(3 - wg) : "memory");
        TSF(5); TS9(2);
        if (PLAG && warp == 5) e_tma(bars + 8 * (B_L + 3), &tmx64, sbase + OFF_X + 2 * X_BYTES + 8192 + 16384, 10 * BK, mt * BM + 128 + 64);
        wgmma_wait<0>();
        TSF(6); TS9(3);
        if (PLAG && wg == 0) {
            if (w4 < 2) e_bulk_p(1, bars + 8 * B_L, W_BYTES / 2, sbase + OFF_X + w4 * X_BYTES, wgrp + (10 * 8 + w4 * 4) * BN);
            else if (w4 == 2) e_tma(bars + 8 * B_L, &tmx64, sbase + OFF_X + 2 * X_BYTES + 8192, 10 * BK, mt * BM + 64);
        }
        unsigned tb; asm volatile("mov.u32 %0, %%clock;" : "=r"(tb));
        auto pst = [&](unsigned t) { unsigned c; do { asm volatile("mov.u32 %0, %%clock;" : "=r"(c)); } while (c - tb < t); };
#pragma unroll
        for (int h = 0; h < (BSP > DSP ? BSP : DSP); h++) {
            if (h < BSP && h < DSP) { if (PSTB && wg == 0) pst(PSB0 + h * PSTB); if (PSTD && wg == 1) pst(h * PSTD); store_half<64 * F_>(p0, o, h); }
            else if (wg == (BSP > DSP ? 0 : 1)) { if (PSTB && wg == 0) pst(PSB0 + h * PSTB); store_half<64 * F_>(p0, o, h); }
        }
        TSF(7);
    }
    {
        if (PLAG == 1 || (PLAG == 3 && wg == 1)) { mbar_wait(bars + 8 * B_L); if (wg == 1) mbar_wait(bars + 8 * (B_L + 3)); }
        asm volatile("bar.sync %0, 256;" ::"r"(2 + wg) : "memory");
        TSF(8);
        const uint32_t b16 = launder();
        wgmma_fence();
#pragma unroll
        for (int i = 0; i < 20; i++) {
            wgmma_rs_n64(p1, af + i * 4, dB(b16, wofs(11 + (i >> 2), i & 3) + 128 * 16));
            if (i % ISTEP2 == 0) {
                const int h0 = BSP + i / ISTEP2, h1 = DSP + i / ISTEP2;
                if (BSP == DSP) { if (h0 < 8) store_half<64 * F_>(p0, o, h0); }
                else {
                    if (h0 < 8) store_half<64 * F_>(p0, o, h0, wg ^ 1);
                    if (h1 < 8) store_half<64 * F_>(p0, o, h1, wg);
                }
            }
        }
        if (PLAG) {
            if (PLAG == 2 || (PLAG == 3 && wg == 0)) { mbar_wait(bars + 8 * B_L); if (wg == 1) mbar_wait(bars + 8 * (B_L + 3)); }
#pragma unroll
            for (int kk = 0; kk < 4; kk++) wgmma_ss_n64(p1, dA(b16, xofs(11, kk, 1)), dB(b16, OFF_X + (kk >> 1) * X_BYTES + (kk & 1) * 2 * CHUNK_BYTES + 128 * 16));
        }
        wgmma_commit();
        if (PLAG) {
#pragma unroll
            for (int kk = 0; kk < 4; kk++) wgmma_ss_n32(p2, dA(b16, xofs(11, kk, 1)), dB(b16, OFF_X + (kk >> 1) * X_BYTES + (kk & 1) * 2 * CHUNK_BYTES + 192 * 16));
        }
        asm volatile("bar.arrive %0, 256;" ::"r"(3 - wg) : "memory");
        wgmma_wait<0>();
        TS9(4);
#pragma unroll
        for (int h = 0; h < ALTS; h++) store_half<64 * F_ + 128>(p1, o, h);
        asm volatile("bar.sync %0, 256;" ::"r"(2 + wg) : "memory");
        wgmma_fence();
#pragma unroll
        for (int i = 0; i < 20; i++) wgmma_rs_n32(p2, af + i * 4, dB(b16, wofs(11 + (i >> 2), i & 3) + 192 * 16));
        wgmma_commit();
        if (wg == 0) asm volatile("bar.arrive 3, 256;" ::: "memory");
#pragma unroll
        for (int h = ALTS; h < 4; h++) store_half<64 * F_ + 128>(p1, o, h);
        wgmma_wait<0>();
        TSK(4, 63); TSF(10);
        store_tile<64 * F_ + 192, 0, 1>(p2, o);
        TSK(4, 77); TSF(11);
    }
}

typedef CUresult (*EncodeTiledFn)(CUtensorMap*, CUtensorMapDataType, cuuint32_t, void*, const cuuint64_t*, const cuuint64_t*, const cuuint32_t*, const cuuint32_t*, CUtensorMapInterleave, CUtensorMapSwizzle, CUtensorMapL2promotion, CUtensorMapFloatOOBfill);

extern "C" void kernel_launch(void* const* d_in, const int* in_sizes, int n_in, void* d_out, int out_size) {
    static EncodeTiledFn enc = nullptr;
    static decltype(&fused_kernel<true>) kern = nullptr;
    static void *p_w = nullptr, *p_flags = nullptr, *p_prof = nullptr;
    if (!enc) {
        void* fn = nullptr; cudaDriverEntryPointQueryResult qr;
        cudaGetDriverEntryPoint("cuTensorMapEncodeTiled", &fn, cudaEnableDefault, &qr);
        enc = (EncodeTiledFn)fn;
        int dev = 0, rsv = 0;
        cudaGetDevice(&dev);
        cudaDeviceGetAttribute(&rsv, cudaDevAttrReservedSharedMemoryPerBlock, dev);
        kern = HARDBASE && rsv == 1024 ? fused_kernel<true> : fused_kernel<false>;
        cudaFuncSetAttribute(kern, cudaFuncAttributeMaxDynamicSharedMemorySize, SMEM_BYTES);
        cudaGetSymbolAddress(&p_w, g_w);
        cudaGetSymbolAddress(&p_flags, g_flags);
    }
    CUtensorMap tmx, tmx64, tmq;
    {
        cuuint64_t gdim[2] = {(cuuint64_t)F_, (cuuint64_t)D_};
        cuuint64_t gstr[1] = {(cuuint64_t)F_ * 4};
        cuuint32_t box[2] = {(cuuint32_t)BN, 16};
        cuuint32_t estr[2] = {1, 1};
        enc(&tmq, CU_TENSOR_MAP_DATA_TYPE_INT32, 2, d_in[1], gdim, gstr, box, estr, CU_TENSOR_MAP_INTERLEAVE_NONE,
            CU_TENSOR_MAP_SWIZZLE_NONE, CU_TENSOR_MAP_L2_PROMOTION_L2_128B, CU_TENSOR_MAP_FLOAT_OOB_FILL_NONE);
    }
    {
        cuuint64_t gdim[2] = {(cuuint64_t)D_, (cuuint64_t)S_};
        cuuint64_t gstr[1] = {(cuuint64_t)D_ * 2};
        cuuint32_t box[2] = {(cuuint32_t)BK, (cuuint32_t)BM};
        cuuint32_t estr[2] = {1, 1};
        enc(&tmx, CU_TENSOR_MAP_DATA_TYPE_BFLOAT16, 2, d_in[0], gdim, gstr, box, estr, CU_TENSOR_MAP_INTERLEAVE_NONE,
            CU_TENSOR_MAP_SWIZZLE_128B, XPROMO, CU_TENSOR_MAP_FLOAT_OOB_FILL_NONE);
        box[1] = 64;
        enc(&tmx64, CU_TENSOR_MAP_DATA_TYPE_BFLOAT16, 2, d_in[0], gdim, gstr, box, estr, CU_TENSOR_MAP_INTERLEAVE_NONE,
            CU_TENSOR_MAP_SWIZZLE_128B, XPROMO, CU_TENSOR_MAP_FLOAT_OOB_FILL_NONE);
    }
    kern<<<128, 256, SMEM_BYTES>>>((const int*)d_in[1], (const unsigned short*)d_in[2], (__nv_bfloat16*)d_out, (uint4*)p_w, (unsigned*)p_flags, 0x80000000u, tmq, tmx64, tmx
    );
    (void)p_prof;
}
```

```cpp
#include <cuda_runtime.h>
#include <cuda_bf16.h>
#include <cuda.h>
#include <stdint.h>
#include <stdio.h>

#define PR1 1100
#define PX0 1150
#define PX0B 2700
#define PR2 1700
#define W1D 150
#define W2D 200
#define CSP 10
#define PSTA 110
#define PSF 2
#define L11 4
#define L12 7
#define DSP 5
#define PSB0 200
#define PSTB 110
#define PSTD 100

#define NOHARD 0

constexpr int S_ = 2048, D_ = 1024, F_ = 3584;
constexpr int BM = 256, BN = 224, BK = 64;
constexpr int X_BYTES = BM * BK * 2;
constexpr int W_BYTES = BN * BK * 2;
constexpr int CHUNK_BYTES = BN * 16;
constexpr int SLAB_BYTES = 16 * BN * 4;
constexpr int OFF_X = 0;
constexpr int OFF_W = 3 * X_BYTES;
constexpr int OFF_STG = OFF_W + 3 * W_BYTES;
constexpr int OFF_LUT = OFF_W + 4 * W_BYTES;
constexpr int OFF_BAR = OFF_LUT + 7 * 2048;
constexpr int OFF_PROF = OFF_BAR + 1024;
constexpr int SMEM_BYTES = OFF_PROF + 1024 + 1024;
constexpr int OFF_SLAB0 = OFF_W + 2 * W_BYTES, OFF_SLAB2 = OFF_X + 2 * X_BYTES;
constexpr int B_FULL = 0;
constexpr int B_XV = 12;
constexpr int B_WF = 17;
constexpr int B_EMPTY = 22;
constexpr int B_X0B = 34;
constexpr int B_X15 = 35;
constexpr int B_DQ = 34;
constexpr int B_SLAB = 42;
constexpr int B_LUT = 46;
constexpr int NFAST = 4;
constexpr unsigned long long R_BATCH = 0x60050400ull, W_FLAG = 0x600504000ull;
constexpr unsigned L1_MASK = 0x2E, L2_MASK = 0x1E8;

__device__ __align__(1024) uint4 g_w[(size_t)F_ * D_ / 8];
__device__ __align__(128) unsigned g_flags[16 * 32];

__device__ __forceinline__ uint32_t smem_u32(const void* p) { return (uint32_t)__cvta_generic_to_shared(p); }
__device__ __forceinline__ void mbar_init(uint32_t bar, uint32_t cnt) { asm volatile("mbarrier.init.shared::cta.b64 [%0], %1;" ::"r"(bar), "r"(cnt) : "memory"); }
__device__ __forceinline__ void mbar_wait(uint32_t bar) {
    asm volatile("{\n.reg .pred p;\nWAIT_LOOP:\nmbarrier.try_wait.parity.shared::cta.b64 p, [%0], 0;\n@p bra WAIT_DONE;\nbra WAIT_LOOP;\nWAIT_DONE:\n}" ::"r"(bar) : "memory");
}
__device__ __forceinline__ void e_arrive(uint32_t bar) {
    asm volatile("{\n.reg .pred p;\nelect.sync _|p, 0xffffffff;\n@p mbarrier.arrive.shared::cta.b64 _, [%0];\n}" ::"r"(bar) : "memory");
}
__device__ __forceinline__ void e_expect(uint32_t bar, uint32_t bytes) {
    asm volatile("{\n.reg .pred p;\nelect.sync _|p, 0xffffffff;\n@p mbarrier.arrive.expect_tx.shared::cta.b64 _, [%0], %1;\n}" ::"r"(bar), "r"(bytes) : "memory");
}
__device__ __forceinline__ void e_tma(uint32_t bar, const CUtensorMap* tm, uint32_t d0, int x0, int y0) {
    asm volatile("{\n.reg .pred p;\nelect.sync _|p, 0xffffffff;\n"
                 "@p cp.async.bulk.tensor.2d.shared::cluster.global.mbarrier::complete_tx::bytes [%2], [%1, {%3, %4}], [%0];\n}"
                 ::"r"(bar), "l"(tm), "r"(d0), "r"(x0), "r"(y0) : "memory");
}
__device__ __forceinline__ void e_bulk(uint32_t bar, uint32_t bytes, uint32_t dst, const void* src) {
    asm volatile("{\n.reg .pred p;\nelect.sync _|p, 0xffffffff;\n"
                 "@p mbarrier.arrive.expect_tx.shared::cta.b64 _, [%0], %1;\n"
                 "@p cp.async.bulk.shared::cluster.global.mbarrier::complete_tx::bytes [%2], [%3], %1, [%0];\n}"
                 ::"r"(bar), "r"(bytes), "r"(dst), "l"(src) : "memory");
}
__device__ __forceinline__ void e_bulk_p(uint32_t on, uint32_t bar, uint32_t bytes, uint32_t dst, const void* src) {
    if (on) asm volatile("{\n.reg .pred p;\nelect.sync _|p, 0xffffffff;\n"
                         "@p cp.async.bulk.shared::cluster.global.mbarrier::complete_tx::bytes [%2], [%3], %1, [%0];\n}"
                         ::"r"(bar), "r"(bytes), "r"(dst), "l"(src) : "memory");
}
__device__ __forceinline__ void e_publish(unsigned* flag) {
    asm volatile("{\n.reg .pred p;\nelect.sync _|p, 0xffffffff;\n@p red.release.gpu.global.add.u32 [%0], 1;\n}" ::"l"(flag) : "memory");
}
__device__ __forceinline__ unsigned ld_flag(const unsigned* f) { unsigned v; asm volatile("ld.relaxed.gpu.global.u32 %0, [%1];" : "=r"(v) : "l"(f) : "memory"); return v; }
__device__ __forceinline__ void finish_poll(const unsigned* f, unsigned v, unsigned target) {
    int n = 0;
    while (!__all_sync(0xffffffff, (int)(v - target) >= 0) && ++n < 4000000) v = ld_flag(f);
    asm volatile("fence.acquire.gpu;" ::: "memory");
    asm volatile("fence.proxy.async.global;" ::: "memory");
}
template <typename T> __device__ __forceinline__ T* ptr_add(T* base, uint32_t off) {
    uint64_t r;
    asm("{\n.reg .u32 l, h;\nmov.b64 {l, h}, %1;\nadd.cc.u32 l, l, %2;\naddc.u32 h, h, 0;\nmov.b64 %0, {l, h};\n}" : "=l"(r) : "l"(base), "r"(off));
    return (T*)r;
}
__device__ __forceinline__ void wgmma_fence() { asm volatile("wgmma.fence.sync.aligned;" ::: "memory"); }
__device__ __forceinline__ void wgmma_commit() { asm volatile("wgmma.commit_group.sync.aligned;" ::: "memory"); }
template <int N> __device__ __forceinline__ void wgmma_wait() { asm volatile("wgmma.wait_group.sync.aligned %0;" ::"n"(N) : "memory"); }
__device__ __forceinline__ void wgmma_m64n224k16(float (&d)[112], uint64_t da, uint64_t db, int scale_d) {
    asm volatile(
        "{\n.reg .pred p;\nsetp.ne.b32 p, %114, 0;\n"
        "wgmma.mma_async.sync.aligned.m64n224k16.f32.bf16.bf16 "
        "{%0, %1, %2, %3, %4, %5, %6, %7, %8, %9, %10, %11, %12, %13, %14, %15, "
        "%16, %17, %18, %19, %20, %21, %22, %23, %24, %25, %26, %27, %28, %29, %30, %31, "
        "%32, %33, %34, %35, %36, %37, %38, %39, %40, %41, %42, %43, %44, %45, %46, %47, "
        "%48, %49, %50, %51, %52, %53, %54, %55, %56, %57, %58, %59, %60, %61, %62, %63, "
        "%64, %65, %66, %67, %68, %69, %70, %71, %72, %73, %74, %75, %76, %77, %78, %79, "
        "%80, %81, %82, %83, %84, %85, %86, %87, %88, %89, %90, %91, %92, %93, %94, %95, "
        "%96, %97, %98, %99, %100, %101, %102, %103, %104, %105, %106, %107, %108, %109, %110, %111}, "
        "%112, %113, p, 1, 1, 0, 0;\n}\n"
        : "+f"(d[0]), "+f"(d[1]), "+f"(d[2]), "+f"(d[3]), "+f"(d[4]), "+f"(d[5]), "+f"(d[6]), "+f"(d[7]),
          "+f"(d[8]), "+f"(d[9]), "+f"(d[10]), "+f"(d[11]), "+f"(d[12]), "+f"(d[13]), "+f"(d[14]), "+f"(d[15]),
          "+f"(d[16]), "+f"(d[17]), "+f"(d[18]), "+f"(d[19]), "+f"(d[20]), "+f"(d[21]), "+f"(d[22]), "+f"(d[23]),
          "+f"(d[24]), "+f"(d[25]), "+f"(d[26]), "+f"(d[27]), "+f"(d[28]), "+f"(d[29]), "+f"(d[30]), "+f"(d[31]),
          "+f"(d[32]), "+f"(d[33]), "+f"(d[34]), "+f"(d[35]), "+f"(d[36]), "+f"(d[37]), "+f"(d[38]), "+f"(d[39]),
          "+f"(d[40]), "+f"(d[41]), "+f"(d[42]), "+f"(d[43]), "+f"(d[44]), "+f"(d[45]), "+f"(d[46]), "+f"(d[47]),
          "+f"(d[48]), "+f"(d[49]), "+f"(d[50]), "+f"(d[51]), "+f"(d[52]), "+f"(d[53]), "+f"(d[54]), "+f"(d[55]),
          "+f"(d[56]), "+f"(d[57]), "+f"(d[58]), "+f"(d[59]), "+f"(d[60]), "+f"(d[61]), "+f"(d[62]), "+f"(d[63]),
          "+f"(d[64]), "+f"(d[65]), "+f"(d[66]), "+f"(d[67]), "+f"(d[68]), "+f"(d[69]), "+f"(d[70]), "+f"(d[71]),
          "+f"(d[72]), "+f"(d[73]), "+f"(d[74]), "+f"(d[75]), "+f"(d[76]), "+f"(d[77]), "+f"(d[78]), "+f"(d[79]),
          "+f"(d[80]), "+f"(d[81]), "+f"(d[82]), "+f"(d[83]), "+f"(d[84]), "+f"(d[85]), "+f"(d[86]), "+f"(d[87]),
          "+f"(d[88]), "+f"(d[89]), "+f"(d[90]), "+f"(d[91]), "+f"(d[92]), "+f"(d[93]), "+f"(d[94]), "+f"(d[95]),
          "+f"(d[96]), "+f"(d[97]), "+f"(d[98]), "+f"(d[99]), "+f"(d[100]), "+f"(d[101]), "+f"(d[102]), "+f"(d[103]),
          "+f"(d[104]), "+f"(d[105]), "+f"(d[106]), "+f"(d[107]), "+f"(d[108]), "+f"(d[109]), "+f"(d[110]), "+f"(d[111])
        : "l"(da), "l"(db), "r"(scale_d));
}

__device__ __forceinline__ void wgmma_rs(float (&d)[16], const uint32_t* a, uint64_t db) {
    asm volatile("wgmma.mma_async.sync.aligned.m64n32k16.f32.bf16.bf16 {%0, %1, %2, %3, %4, %5, %6, %7, %8, %9, %10, %11, %12, %13, %14, %15}, {%16, %17, %18, %19}, %20, 1, 1, 1, 0;"
        : "+f"(d[0]), "+f"(d[1]), "+f"(d[2]), "+f"(d[3]), "+f"(d[4]), "+f"(d[5]), "+f"(d[6]), "+f"(d[7]), "+f"(d[8]), "+f"(d[9]), "+f"(d[10]), "+f"(d[11]), "+f"(d[12]), "+f"(d[13]), "+f"(d[14]), "+f"(d[15])
        : "r"(a[0]), "r"(a[1]), "r"(a[2]), "r"(a[3]), "l"(db));
}
__device__ __forceinline__ void wgmma_rs(float (&d)[32], const uint32_t* a, uint64_t db) {
    asm volatile("wgmma.mma_async.sync.aligned.m64n64k16.f32.bf16.bf16 {%0, %1, %2, %3, %4, %5, %6, %7, %8, %9, %10, %11, %12, %13, %14, %15, %16, %17, %18, %19, %20, %21, %22, %23, %24, %25, %26, %27, %28, %29, %30, %31}, {%32, %33, %34, %35}, %36, 1, 1, 1, 0;"
        : "+f"(d[0]), "+f"(d[1]), "+f"(d[2]), "+f"(d[3]), "+f"(d[4]), "+f"(d[5]), "+f"(d[6]), "+f"(d[7]), "+f"(d[8]), "+f"(d[9]), "+f"(d[10]), "+f"(d[11]), "+f"(d[12]), "+f"(d[13]), "+f"(d[14]), "+f"(d[15]), "+f"(d[16]), "+f"(d[17]), "+f"(d[18]), "+f"(d[19]), "+f"(d[20]), "+f"(d[21]), "+f"(d[22]), "+f"(d[23]), "+f"(d[24]), "+f"(d[25]), "+f"(d[26]), "+f"(d[27]), "+f"(d[28]), "+f"(d[29]), "+f"(d[30]), "+f"(d[31])
        : "r"(a[0]), "r"(a[1]), "r"(a[2]), "r"(a[3]), "l"(db));
}
__device__ __forceinline__ void wgmma_rs(float (&d)[64], const uint32_t* a, uint64_t db) {
    asm volatile("wgmma.mma_async.sync.aligned.m64n128k16.f32.bf16.bf16 {%0, %1, %2, %3, %4, %5, %6, %7, %8, %9, %10, %11, %12, %13, %14, %15, %16, %17, %18, %19, %20, %21, %22, %23, %24, %25, %26, %27, %28, %29, %30, %31, %32, %33, %34, %35, %36, %37, %38, %39, %40, %41, %42, %43, %44, %45, %46, %47, %48, %49, %50, %51, %52, %53, %54, %55, %56, %57, %58, %59, %60, %61, %62, %63}, {%64, %65, %66, %67}, %68, 1, 1, 1, 0;"
        : "+f"(d[0]), "+f"(d[1]), "+f"(d[2]), "+f"(d[3]), "+f"(d[4]), "+f"(d[5]), "+f"(d[6]), "+f"(d[7]), "+f"(d[8]), "+f"(d[9]), "+f"(d[10]), "+f"(d[11]), "+f"(d[12]), "+f"(d[13]), "+f"(d[14]), "+f"(d[15]), "+f"(d[16]), "+f"(d[17]), "+f"(d[18]), "+f"(d[19]), "+f"(d[20]), "+f"(d[21]), "+f"(d[22]), "+f"(d[23]), "+f"(d[24]), "+f"(d[25]), "+f"(d[26]), "+f"(d[27]), "+f"(d[28]), "+f"(d[29]), "+f"(d[30]), "+f"(d[31]), "+f"(d[32]), "+f"(d[33]), "+f"(d[34]), "+f"(d[35]), "+f"(d[36]), "+f"(d[37]), "+f"(d[38]), "+f"(d[39]), "+f"(d[40]), "+f"(d[41]), "+f"(d[42]), "+f"(d[43]), "+f"(d[44]), "+f"(d[45]), "+f"(d[46]), "+f"(d[47]), "+f"(d[48]), "+f"(d[49]), "+f"(d[50]), "+f"(d[51]), "+f"(d[52]), "+f"(d[53]), "+f"(d[54]), "+f"(d[55]), "+f"(d[56]), "+f"(d[57]), "+f"(d[58]), "+f"(d[59]), "+f"(d[60]), "+f"(d[61]), "+f"(d[62]), "+f"(d[63])
        : "r"(a[0]), "r"(a[1]), "r"(a[2]), "r"(a[3]), "l"(db));
}

__device__ __forceinline__ uint32_t pack_bf16(float lo, float hi) {
    uint32_t r; asm("cvt.rn.bf16x2.f32 %0, %1, %2;" : "=r"(r) : "f"(hi), "f"(lo)); return r;
}
__device__ __forceinline__ uint32_t lds32(uint32_t a) { uint32_t v; asm volatile("ld.shared.b32 %0, [%1];" : "=r"(v) : "r"(a)); return v; }
__device__ __forceinline__ void sts32(uint32_t a, uint32_t v) { asm volatile("st.shared.b32 [%0], %1;" ::"r"(a), "r"(v) : "memory"); }
__device__ __forceinline__ void sts128(uint32_t a, uint4 v) { asm volatile("st.shared.v4.b32 [%0], {%1,%2,%3,%4};" ::"r"(a), "r"(v.x), "r"(v.y), "r"(v.z), "r"(v.w) : "memory"); }
__device__ __forceinline__ void stg128(void* p, uint4 v) { asm volatile("st.global.v4.b32 [%0], {%1,%2,%3,%4};" ::"l"(p), "r"(v.x), "r"(v.y), "r"(v.z), "r"(v.w) : "memory"); }
__device__ __forceinline__ void cp16(uint32_t dst, const void* src) { asm volatile("cp.async.cg.shared.global [%0], [%1], 16;" ::"r"(dst), "l"(src) : "memory"); }
__device__ __forceinline__ void cp_commit() { asm volatile("cp.async.commit_group;" ::: "memory"); }
template <int N> __device__ __forceinline__ void cp_wait() { asm volatile("cp.async.wait_group %0;" ::"n"(N) : "memory"); }
__device__ __forceinline__ uint4 dequant8(uint32_t raw, uint32_t lut_a) {
    uint32_t v[8];
#pragma unroll
    for (int i = 0; i < 8; i++) v[i] = lds32(raw + i * 128);
#pragma unroll
    for (int i = 0; i < 8; i++) v[i] = lds32(lut_a + v[i] * 128);
    uint4 o;
    o.x = __byte_perm(v[0], v[1], 0x5410); o.y = __byte_perm(v[2], v[3], 0x5410);
    o.z = __byte_perm(v[4], v[5], 0x5410); o.w = __byte_perm(v[6], v[7], 0x5410);
    return o;
}
__device__ __forceinline__ uint32_t prmt(uint32_t a, uint32_t b, uint32_t c) { uint32_t r; asm("prmt.b32 %0, %1, %2, %3;" : "=r"(r) : "r"(a), "r"(b), "r"(c)); return r; }
__device__ __forceinline__ uint4 lookup8_reg(const uint32_t* c, const uint32_t (&T)[8]) {
    uint32_t o[4];
#pragma unroll
    for (int h = 0; h < 2; h++) {
        const uint32_t sel = c[4 * h] + c[4 * h + 1] * 16 + c[4 * h + 2] * 256 + c[4 * h + 3] * 4096;
        const uint32_t s7 = sel & 0x7777u;
        uint32_t m;
        asm("lop3.b32 %0, %1, %2, 0x3210, 0xEA;" : "=r"(m) : "r"(sel >> 1), "r"(0x4444u));
        const uint32_t lo = prmt(prmt(T[0], T[1], s7), prmt(T[2], T[3], s7), m);
        const uint32_t hi = prmt(prmt(T[4], T[5], s7), prmt(T[6], T[7], s7), m);
        o[2 * h] = prmt(lo, hi, 0x5140u); o[2 * h + 1] = prmt(lo, hi, 0x7362u);
    }
    return make_uint4(o[0], o[1], o[2], o[3]);
}
template <int N>
__device__ __forceinline__ void pack_half(const float (&acc)[N], int H, uint32_t* r) {
    const int b = (H >> 1) * 16 + (H & 1) * 2;
#pragma unroll
    for (int i = 0; i < 4; i++) asm volatile("cvt.rn.bf16x2.f32 %0, %1, %2;" : "=r"(r[i]) : "f"(acc[b + 4 * i + 1]), "f"(acc[b + 4 * i]));
}
__device__ __forceinline__ void store_packed(__nv_bfloat16* o, int H, const uint32_t* r, int on = 1) {
    asm volatile("{\n.reg .pred p;\nsetp.ne.b32 p, %5, 0;\n@p st.global.v4.b32 [%0], {%1,%2,%3,%4};\n}"
                 ::"l"(o + (H & 1) * 8 * F_ + (H >> 1) * 32), "r"(r[0]), "r"(r[1]), "r"(r[2]), "r"(r[3]), "r"(on) : "memory");
}
template <int N>
__device__ __forceinline__ void store_half(const float (&acc)[N], __nv_bfloat16* o, int H, int on = 1) {
    const int b = (H >> 1) * 16 + (H & 1) * 2;
    const uint32_t r[4] = {pack_bf16(acc[b], acc[b + 1]), pack_bf16(acc[b + 4], acc[b + 5]), pack_bf16(acc[b + 8], acc[b + 9]), pack_bf16(acc[b + 12], acc[b + 13])};
    store_packed(o, H, r, on);
}
__device__ __forceinline__ unsigned clk() { unsigned c; asm volatile("mov.u32 %0, %%clock;" : "=r"(c)); return c; }
__device__ __forceinline__ void wait_until(unsigned t0, unsigned dt) { while (clk() - t0 < dt) {} }

#define TSK(w, i)
#define TS8(i)
#define TSW(w, i)
#define TS9(i)

template <bool HARD>
__global__ void __launch_bounds__(256, 1)
fused_kernel(const int* __restrict__ qw, const unsigned short* __restrict__ lut, __nv_bfloat16* __restrict__ out,
             uint4* __restrict__ wscr, unsigned* __restrict__ flags,
             const __grid_constant__ CUtensorMap tmq, const __grid_constant__ CUtensorMap tmx64, const __grid_constant__ CUtensorMap tmx
) {
    extern __shared__ uint8_t smem_raw[];
    const uint32_t sbase = HARD ? 1024u : (smem_u32(smem_raw) + 1023) & ~1023u;
    const uint32_t bars = sbase + OFF_BAR;
    const int tid = threadIdx.x, lane = tid & 31;
    const int mt = blockIdx.x & 7, g = blockIdx.x >> 3;
    const unsigned clk0 = clk();
    const int warp = __shfl_sync(0xffffffff, tid >> 5, 0);
    if (tid >= 224) {
        asm volatile("{\n.reg .pred p;\nelect.sync _|p, 0xffffffff;\n"
                     "@p mbarrier.init.shared::cta.b64 [%0], 1;\n"
                     "@p fence.mbarrier_init.release.cluster;\n"
                     "@p mbarrier.arrive.expect_tx.shared::cta.b64 _, [%0], %1;\n"
                     "@p cp.async.bulk.tensor.2d.shared::cluster.global.mbarrier::complete_tx::bytes [%3], [%2, {%4, 0}], [%0];\n}"
                     ::"r"(bars + 8 * B_SLAB), "n"(SLAB_BYTES), "l"(&tmq), "r"(sbase + OFF_SLAB0), "r"(g * BN) : "memory");
    } else {
        const unsigned short* lp = ptr_add(lut, ((lane >> 2) * F_ + g * BN + (tid & ~31) + (lane & 3) * 8) * 2);
        asm volatile("cp.async.cg.shared.global [%0], [%1], 16;\ncp.async.cg.shared.global [%0+512], [%1+57344], 16;\ncp.async.commit_group;"
                     ::"r"(sbase + OFF_STG + (tid >> 5) * 4096 + lane * 16), "l"(lp) : "memory");
    }
    const int sl = warp - 3;
    auto load_slab = [&]() {
        e_tma(bars + 8 * (B_SLAB + sl), &tmq, sbase + (sl < 2 ? OFF_SLAB0 : OFF_SLAB2 - 2 * SLAB_BYTES) + sl * SLAB_BYTES, g * BN, sl * 16);
    };
    if (warp >= 4 && warp < 7) {
        asm volatile("{\n.reg .pred p;\nelect.sync _|p, 0xffffffff;\n"
                     "@p mbarrier.init.shared::cta.b64 [%0], 1;\n"
                     "@p fence.mbarrier_init.release.cluster;\n"
                     "@p mbarrier.arrive.expect_tx.shared::cta.b64 _, [%0], %1;\n}"
                     ::"r"(bars + 8 * (B_SLAB + sl)), "n"(SLAB_BYTES) : "memory");
        if (sl < 2) load_slab();
    } else if (warp < 2) {
        asm volatile("{\n.reg .pred p;\nelect.sync _|p, 0xffffffff;\n"
                     "@p mbarrier.init.shared::cta.b64 [%0], %1;\n"
                     "@p fence.mbarrier_init.release.cluster;\n}" ::"r"(bars + 8 * (warp ? B_LUT : B_FULL)), "r"(8 - warp) : "memory");
    }
    asm volatile("bar.sync 1, 256;" ::: "memory");
    const int wg = warp >> 2;

    const int fl = 8 * ((lane & 7) >> 1) + 2 * (lane >> 3) + (lane & 1);
    const uint32_t lut_a = sbase + OFF_LUT + warp * 2048 + lane * 4;
    const uint32_t stg = sbase + OFF_STG + warp * 4096;
    unsigned* myflags = flags + g * 32;
    const uint4* wgrp = wscr + (size_t)g * 128 * BN;
    unsigned target = 0;

    auto issue_x = [&](int s, int slot) {
        e_tma(bars + 8 * (B_FULL + s), &tmx, sbase + OFF_X + slot * X_BYTES, s * BK, mt * BM);
    };
    auto issue_xv = [&](int v, int w, uint32_t bar) {
        const uint32_t dst = sbase + OFF_X + (v & 1) * X_BYTES + w * 16384;
        const int k0 = (12 + 2 * (v & 1)) * BK, r0 = mt * BM + w * 128 + ((v >> 1) & 1) * 64;
        e_tma(bar, &tmx64, dst, k0, r0);
        e_tma(bar, &tmx64, dst + 8192, k0 + BK, r0);
    };
    auto issue_w = [&](int s, int slot, int bar) {
        e_bulk(bars + 8 * bar, W_BYTES, sbase + OFF_W + slot * W_BYTES, wgrp + s * 8 * BN);
    };
    auto load_blk = [&](int t, int c) {
        const int* src = ptr_add(qw, (uint32_t)(((t * BK + mt * 8 + (lane >> 3)) * F_ + g * BN + c * 32 + (lane & 7) * 4) * 4));
        asm volatile("cp.async.cg.shared.global [%0], [%1], 16;\ncp.async.cg.shared.global [%0+512], [%1+57344], 16;"
                     ::"r"(sbase + OFF_STG + c * 4096 + (t & 3) * 1024 + lane * 16), "l"(src) : "memory");
    };
    auto load_raw = [&](int t) { if (t < 16) load_blk(t, warp); cp_commit(); };
    auto unit = [&](int t, int c) { return ptr_add(wscr, (uint32_t)(((g * 128 + t * 8 + mt) * BN + c * 32 + lane) * 16)); };
    auto foreign2 = [&]() {
        const int c = warp - 4;
        stg128(unit(2, c), dequant8(sbase + OFF_STG + c * 4096 + 2 * 1024 + fl * 4, sbase + OFF_LUT + c * 2048 + lane * 4));
    };
    auto coop = [&](int t) {
        cp_wait<1>();
        __syncwarp();
        load_raw(t + 2);
        stg128(unit(t, warp), dequant8(stg + (t & 3) * 1024 + fl * 4, lut_a));
    };

    if (warp == 7) {
        if (lane == 0) {
            asm volatile("prefetch.tensormap [%0];" ::"l"(&tmx) : "memory");
            asm volatile("prefetch.tensormap [%0];" ::"l"(&tmx64) : "memory");
        }
        __syncwarp();
        auto x0 = [&](int w, uint32_t bar) {
            e_expect(bar, X_BYTES / 2);
            e_tma(bar, &tmx64, sbase + OFF_X + w * 16384, 0, mt * BM + w * 128);
            e_tma(bar, &tmx64, sbase + OFF_X + w * 16384 + 8192, 0, mt * BM + w * 128 + 64);
        };
        wait_until(clk0, PX0);
        x0(0, bars + 8 * B_FULL);
        target = ld_flag(myflags + 6);
        wait_until(clk0, PR2);
        load_blk(2, 3);
        cp_commit();
        mbar_wait(bars + 8 * B_LUT);
        wait_until(clk0, PX0B);
        x0(1, bars + 8 * B_X0B);
        target = (target | 7) + 1;
        mbar_wait(bars + 8 * B_FULL);
        issue_x(1, 1);
        cp_wait<0>();
        __syncwarp();
        foreign2();
        TSW(7, 3);
    } else {
        if (wg == 1 && sl >= 2) load_slab();
        if (lane == 0) {
#pragma unroll
            for (int i = 0; i < 6; i++) {
                const int b = 1 + warp * 6 + i;
                if (b < B_SLAB) mbar_init(bars + 8 * b, b < B_DQ + 4 ? 1 : 7);
                if (b < B_XV) asm volatile("mbarrier.arrive.expect_tx.shared::cta.b64 _, [%0], %1;" ::"r"(bars + 8 * b), "r"(X_BYTES + W_BYTES) : "memory");
            }
            asm volatile("fence.mbarrier_init.release.cluster;" ::: "memory");
        }
        __syncwarp();
        wait_until(clk0, PR1);
        load_raw(1);
        uint32_t lv[16], v[32], T[8];
        cp_wait<1>();
        __syncwarp();
#pragma unroll
        for (int i = 0; i < 16; i++) asm volatile("ld.shared.u16 %0, [%1];" : "=r"(lv[i]) : "r"(stg + i * 64 + fl * 2));
#pragma unroll
        for (int i = 0; i < 16; i++) lv[i] = lv[i] ? lv[i] : 0x8000u;
#pragma unroll
        for (int i = 0; i < 4; i++) {
            const uint32_t p01 = prmt(lv[4 * i], lv[4 * i + 1], 0x5140u), p23 = prmt(lv[4 * i + 2], lv[4 * i + 3], 0x5140u);
            T[i] = prmt(p01, p23, 0x5410u); T[4 + i] = prmt(p01, p23, 0x7632u);
        }
        TSW(0, 7);
#pragma unroll
        for (int i = 0; i < 16; i++) sts32(lut_a + i * 128, lv[i]);
        __syncwarp();
        e_arrive(bars + 8 * B_LUT);
        auto own_task = [&](int t) {
            __syncwarp();
            uint32_t c[8];
#pragma unroll
            for (int i = 0; i < 8; i++) c[i] = lds32(stg + t * 1024 + fl * 4 + i * 128);
            stg128(unit(t, warp), lookup8_reg(c, T));
        };
        auto piece_ld = [&](int j) {
            mbar_wait(bars + 8 * (B_SLAB + j));
#pragma unroll
            for (int i = 0; i < 16; i++) v[(j & 1) * 16 + i] = lds32(sbase + (j < 2 ? OFF_SLAB0 : OFF_SLAB2) + (j & 1) * SLAB_BYTES + i * (BN * 4) + (warp * 32 + fl) * 4);
        };
        auto piece_st = [&](int j) {
            const uint32_t dst = sbase + OFF_W + j * 2 * CHUNK_BYTES + (warp * 32 + lane) * 16;
            sts128(dst, lookup8_reg(v + (j & 1) * 16, T));
            sts128(dst + CHUNK_BYTES, lookup8_reg(v + (j & 1) * 16 + 8, T));
            TSW(0, 8 + j);
        };
        piece_ld(0);
        if (wg == 1) { load_blk(2, warp); load_blk(2, warp - 4); cp_commit(); }
        piece_st(0);
        piece_ld(1);
        piece_ld(2);
        piece_st(1);
        piece_ld(3);
        if (wg == 0) load_raw(3);
        piece_st(2);
        piece_st(3);
        asm volatile("fence.proxy.async.shared::cta;" ::: "memory");
        __syncwarp();
        e_arrive(bars + 8 * B_FULL);
        cp_wait<1>();
        own_task(1);
        TSW(0, 14);
        if (wg == 1) {
            load_raw(3);
            cp_wait<1>();
            own_task(2);
            load_raw(4);
            mbar_wait(bars + 8 * B_LUT);
            foreign2();
        }
        TSW(4, 12);
    }

    float acc0[112], acc1[112];
    const uint64_t descA_hi = ((uint64_t)1 << 62) | ((uint64_t)(1024 >> 4) << 32) | ((uint64_t)1 << 16);
    const uint64_t descB_hi = ((uint64_t)(128 >> 4) << 32) | ((uint64_t)(CHUNK_BYTES >> 4) << 16);
    const uint32_t a16 = ((sbase & 0x3FFFF) >> 4) + wg * 1024 + (uint32_t)descA_hi, b16w = (((sbase + OFF_W) & 0x3FFFF) >> 4) + (uint32_t)descB_hi;
    auto dscA = [&](uint32_t lo) { return (descA_hi & 0xFFFFFFFF00000000ull) | lo; };
    auto dscB = [&](uint32_t lo) { return (descB_hi & 0xFFFFFFFF00000000ull) | lo; };
    uint32_t xo = 0, wo = 0, wo_prev = 2 * W_BYTES;
    const uint4* wnext = wgrp + 2 * 8 * BN;
    auto validate = [&](int t) {
        const uint32_t a = sbase + OFF_W + wo;
        for (int n = 0; n < 2000000; n++) {
            uint32_t m = 0xffffffffu;
#pragma unroll
            for (int i = 0; i < 7; i++) m = min(m, lds32(a + tid * 32 + (lane >> 2) * 4 + i * 4096));
            if (__all_sync(0xffffffff, m != 0)) break;
            const uint4* src = ptr_add(wgrp, (uint32_t)((t * 8 * BN + warp * 64 + lane) * 16));
#pragma unroll 1
            for (int i = 0; i < 14; i++) cp16(a + (warp * 64 + lane + (i >> 1) * 256 + (i & 1) * 32) * 16, src + (i >> 1) * 256 + (i & 1) * 32);
            cp_commit();
            cp_wait<0>();
            asm volatile("fence.proxy.async.shared::cta;" ::: "memory");
            __syncwarp();
        }
    };
    auto batch = [&](int s, bool in_loop) {
        mbar_wait(bars + 8 * (B_FULL + s));
        if (!in_loop && s == 0 && wg == 1) mbar_wait(bars + 8 * B_X0B);
        if (in_loop && wg == 0 && s <= NFAST) validate(s);
        if (s + wg > 0) asm volatile("bar.sync %0, 256;" ::"r"(2 + wg) : "memory");
        TSW(0, 16 + s); TSW(4, 48 + s); TS8(16 + s);
        const uint32_t al = a16 + (xo >> 4), bl = b16w + (wo >> 4);
        wgmma_fence();
#pragma unroll
        for (int kk = 0; kk < 4; kk++) {
            const uint64_t db = dscB(bl + kk * (2 * CHUNK_BYTES >> 4));
            wgmma_m64n224k16(acc0, dscA(al + kk * 2), db, in_loop || (s | kk) != 0);
            wgmma_m64n224k16(acc1, dscA(al + kk * 2 + (8192 >> 4)), db, in_loop || (s | kk) != 0);
        }
        wgmma_commit();
        asm volatile("bar.arrive %0, 256;" ::"r"(3 - wg) : "memory");
        TSW(0, 32 + s); TSW(4, 64 + s);
    };
    auto advance = [&]() {
        wo_prev = wo;
        xo = xo == 2 * X_BYTES ? 0 : xo + X_BYTES;
        wo = wo == 2 * W_BYTES ? 0 : wo + W_BYTES;
        wnext += 8 * BN;
    };
    batch(0, false);
#pragma unroll 1
    for (int s = 0; s < 9; s++) {
        const uint32_t bs = bars + 8 * s;
        if (warp == 7) {
            const int fb = (int)(W_FLAG >> (4 * s)) & 15, pb = (int)(R_BATCH >> (4 * s)) & 15;
            unsigned* fp = ptr_add(myflags, fb * 4);
            unsigned fv = target;
            const uint32_t l1 = (L1_MASK >> s) & 1, l2 = (L2_MASK >> s) & 1;
            if (fb) fv = ld_flag(fp);
            else e_bulk_p(l1, bs + 8 * (B_FULL + 2), W_BYTES, sbase + OFF_W + wo_prev, wnext);
            if (s == 0) {
                issue_x(2, 2);
                wait_until(clk(), W2D);
                e_bulk_p(1, bs + 8 * (B_FULL + 2), W_BYTES, sbase + OFF_W + wo_prev, wnext);
            }
            TSW(7, 112 + s);
            if (pb) {
                mbar_wait(bars + 8 * (B_DQ + pb));
                mbar_wait(bs + 8 * B_EMPTY);
                e_publish(ptr_add(myflags, pb * 4));
            } else {
                if (fb) {
                    finish_poll(fp, fv, target);
                    e_bulk_p(l1, bs + 8 * (B_FULL + 2), W_BYTES, sbase + OFF_W + wo_prev, wnext);
                }
                mbar_wait(bs + 8 * B_EMPTY);
                if (s == 8) {
                    issue_w(12, 3, B_WF);
                    e_bulk(bars + 8 * (B_WF + 3), W_BYTES / 2, sbase + OFF_LUT, wgrp + 15 * 8 * BN);
                }
            }
            wgmma_wait<0>();
            e_bulk_p(l2, bs + 8 * (B_FULL + 3), W_BYTES, sbase + OFF_W + wo, wnext + 8 * BN);
            e_tma(bs + 8 * (B_FULL + 3), &tmx, sbase + OFF_X + xo, (s + 3) * BK, mt * BM);
            TSW(7, 96 + s);
        } else {
            const int r = s + wg;
            if (r == 0) {
                load_raw(4);
                if (warp == 3) {
                    wait_until(clk(), W1D);
                    e_bulk_p(1, bars + 8 * (B_FULL + 1), W_BYTES, sbase + OFF_W + W_BYTES, wgrp + 8 * BN);
                }
            }
            if (wg == 0 && s < 2) coop(s + 3);
            else if (r < 8) { coop(2 * r + 1); if (r < 7) coop(2 * r + 2); }
            const int b = (int)(R_BATCH >> (4 * r)) & 15;
            if (b) { __syncwarp(); e_arrive(bars + 8 * (B_DQ + b)); }
            TSW(0, 80 + s);
            wgmma_wait<0>();
            if (warp == 3) e_arrive(bs + 8 * B_EMPTY);
        }
        advance();
        batch(s + 1, true);
    }
    {
        if (warp == 7) mbar_wait(bars + 8 * (B_EMPTY + 9));
        wgmma_wait<0>();
        if (warp == 3) e_arrive(bars + 8 * (B_EMPTY + 9));
        if (warp == 7) {
            issue_w(13, 0, B_WF + 1);
            e_expect(bars + 8 * B_XV, X_BYTES);
            issue_xv(12, 0, bars + 8 * B_XV); issue_xv(12, 1, bars + 8 * B_XV);
        }
        advance();
        batch(10, false);
        if (warp == 7) mbar_wait(bars + 8 * (B_EMPTY + 10));
        else {
            mbar_wait(bars + 8 * (B_FULL + 11));
#pragma unroll
            for (int t = 1; t <= NFAST; t++) stg128(unit(t, warp), make_uint4(0, 0, 0, 0));
        }
        wgmma_wait<0>();
        if (warp == 3) e_arrive(bars + 8 * (B_EMPTY + 10));
    }

    const int w4 = warp & 3;
    __nv_bfloat16* o = ptr_add(out, (uint32_t)(((mt * BM + wg * 128 + w4 * 16 + (lane >> 2)) * F_ + g * BN + (lane & 3) * 8) * 2));
    auto wofs = [](int st, int kk) -> uint32_t {
        return st < 15 ? OFF_W + (st == 11 ? 2 : st == 12 ? 3 : st - 13) * W_BYTES + kk * 2 * CHUNK_BYTES
                       : kk < 2 ? OFF_LUT + kk * 2 * CHUNK_BYTES : OFF_X + 2 * X_BYTES + (kk - 2) * 16384;
    };
    auto xofs = [](int st, int kk, int r) -> uint32_t {
        return (st == 11 ? 2 * X_BYTES + r * 8192 : ((st - 12) >> 1) * X_BYTES + (st & 1) * 8192) + kk * 32;
    };
    auto launder = [&]() { uint32_t b16 = (sbase & 0x3FFFF) >> 4; asm volatile("mov.u32 %0, %0;" : "+r"(b16)); return b16; };
    auto dA = [&](uint32_t b16, uint32_t ofs) { return dscA(b16 + wg * 1024 + (ofs >> 4) + (uint32_t)descA_hi); };
    auto dB = [&](uint32_t b16, uint32_t ofs) { return dscB(b16 + (ofs >> 4) + (uint32_t)descB_hi); };
    {
        mbar_wait(bars + 8 * (B_FULL + 11));
        asm volatile("bar.sync %0, 256;" ::"r"(2 + wg) : "memory");
        const uint32_t b16 = launder();
        wgmma_fence();
#pragma unroll
        for (int kk = 0; kk < 4; kk++) wgmma_m64n224k16(acc0, dA(b16, xofs(11, kk, 0)), dB(b16, wofs(11, kk)), 1);
        wgmma_commit();
        asm volatile("bar.arrive %0, 256;" ::"r"(3 - wg) : "memory");
        if (warp == 7) {
            issue_w(14, 1, B_WF + 2);
            e_expect(bars + 8 * (B_XV + 1), X_BYTES);
            issue_xv(13, 0, bars + 8 * (B_XV + 1)); issue_xv(13, 1, bars + 8 * (B_XV + 1));
            mbar_wait(bars + 8 * (B_EMPTY + 11));
        }
        wgmma_wait<0>();
        if (warp == 3) e_arrive(bars + 8 * (B_EMPTY + 11));
        if (warp == 7) {
            e_bulk(bars + 8 * (B_WF + 4), 2 * CHUNK_BYTES, sbase + wofs(15, 2), wgrp + (15 * 8 + 4) * BN);
            e_bulk(bars + 8 * (B_XV + 4), 2 * CHUNK_BYTES, sbase + wofs(15, 3), wgrp + (15 * 8 + 6) * BN);
        }
    }
    {
        asm volatile("bar.sync %0, 256;" ::"r"(2 + wg) : "memory");
        TSK(0, 28);
        const uint32_t b16 = launder();
#pragma unroll
        for (int st = 12; st < 16; st++) {
            if (!(st & 1)) mbar_wait(bars + 8 * (B_XV + ((st - 12) >> 1)));
            mbar_wait(bars + 8 * (B_WF + st - 12));
            if (!(st & 1)) wgmma_fence();
#pragma unroll
            for (int kk = 0; kk < 4; kk++) {
                if (st == 15 && kk >= 2) mbar_wait(bars + 8 * (kk == 2 ? B_WF + 4 : B_XV + 4));
                wgmma_m64n224k16(acc0, dA(b16, xofs(st, kk, 0)), dB(b16, wofs(st, kk)), 1);
            }
            if (st & 1) wgmma_commit();
        }
        asm volatile("bar.arrive %0, 256;" ::"r"(3 - wg) : "memory");
    }
    float p0[64], p1[32], p2[16];
#pragma unroll
    for (int i = 0; i < 64; i++) asm volatile("add.f32 %0, %1, 0f00000000;" : "=f"(p0[i]) : "f"(acc1[i]));
#pragma unroll
    for (int i = 0; i < 32; i++) asm volatile("add.f32 %0, %1, 0f00000000;" : "=f"(p1[i]) : "f"(acc1[64 + i]));
#pragma unroll
    for (int i = 0; i < 16; i++) asm volatile("add.f32 %0, %1, 0f00000000;" : "=f"(p2[i]) : "f"(acc1[96 + i]));
    wgmma_wait<1>();
    if (w4 == 3) { e_expect(bars + 8 * (B_XV + 2 + wg), X_BYTES / 2); issue_xv(14, wg, bars + 8 * (B_XV + 2 + wg)); }
    wgmma_wait<0>();
    if (w4 == 3) { e_expect(bars + 8 * (B_X15 + wg), X_BYTES / 2); issue_xv(15, wg, bars + 8 * (B_X15 + wg)); }
    TS9(0);
    uint32_t af[80], pk[(14 - CSP) * 4];
    const uint32_t lm = sbase + wg * 16384 + (w4 * 16 + (lane & 15)) * 128 + (((lane >> 4) ^ (lane & 7)) << 4);
    auto ldfrag = [&](int st) {
#pragma unroll
        for (int kk = 0; kk < 4; kk++) {
            uint32_t* r = af + ((st - 11) * 4 + kk) * 4;
            asm volatile("ldmatrix.sync.aligned.m8n8.x4.shared.b16 {%0,%1,%2,%3}, [%4];" : "=r"(r[0]), "=r"(r[1]), "=r"(r[2]), "=r"(r[3])
                         : "r"((lm ^ (kk << 5)) + xofs(st, 0, 1)) : "memory");
        }
    };
    unsigned tb = clk();
#pragma unroll
    for (int h = 0; h < CSP; h++) {
        if (h >= PSF) wait_until(tb, (h - PSF + 1) * PSTA);
        store_half(acc0, o, h);
        if (h == L11) ldfrag(11);
        if (h == L12) { mbar_wait(bars + 8 * (B_XV + 2 + wg)); ldfrag(12); }
    }
#pragma unroll
    for (int h = CSP; h < 14; h++) pack_half(acc0, h, pk + (h - CSP) * 4);
    asm volatile("bar.sync %0, 256;" ::"r"(2 + wg) : "memory");
    uint32_t b16 = launder();
#pragma unroll
    for (int st = 11; st < 16; st++) {
        wgmma_fence();
#pragma unroll
        for (int kk = 0; kk < 4; kk++) {
            const int i = (st - 11) * 4 + kk;
            wgmma_rs(p0, af + i * 4, dB(b16, wofs(st, kk)));
            if (i == 0) TS9(1);
            if (kk == 0 && st < 14) {
                if (st == 12) mbar_wait(bars + 8 * (B_X15 + wg));
                ldfrag(st + 2);
            }
            if (!(i & 1) && CSP + i / 2 < 14) store_packed(o, CSP + i / 2, pk + (i / 2) * 4);
        }
    }
    wgmma_commit();
    asm volatile("bar.arrive %0, 256;" ::"r"(3 - wg) : "memory");
    TS9(2);
    wgmma_wait<0>();
    TS9(3);
    tb = clk();
#pragma unroll
    for (int h = 0; h < DSP; h++) { wait_until(tb, wg ? h * PSTD : PSB0 + h * PSTB); store_half(p0, o + 64 * F_, h); }
    if (wg == 0) {
#pragma unroll
        for (int h = DSP; h < 8; h++) { wait_until(tb, PSB0 + h * PSTB); store_half(p0, o + 64 * F_, h); }
    }
    asm volatile("bar.sync %0, 256;" ::"r"(2 + wg) : "memory");
    b16 = launder();
    wgmma_fence();
#pragma unroll
    for (int i = 0; i < 20; i++) {
        wgmma_rs(p1, af + i * 4, dB(b16, wofs(11 + (i >> 2), i & 3) + 128 * 16));
        if (!(i & 1) && DSP + i / 2 < 8) store_half(p0, o + 64 * F_, DSP + i / 2, wg);
    }
    wgmma_commit();
    asm volatile("bar.arrive %0, 256;" ::"r"(3 - wg) : "memory");
    wgmma_wait<0>();
    TS9(4);
#pragma unroll
    for (int h = 0; h < 4; h++) store_half(p1, o + 64 * F_ + 128, h);
    asm volatile("bar.sync %0, 256;" ::"r"(2 + wg) : "memory");
    wgmma_fence();
#pragma unroll
    for (int i = 0; i < 20; i++) wgmma_rs(p2, af + i * 4, dB(b16, wofs(11 + (i >> 2), i & 3) + 192 * 16));
    wgmma_commit();
    if (wg == 0) asm volatile("bar.arrive 3, 256;" ::: "memory");
    wgmma_wait<0>();
    TSK(4, 63);
    store_half(p2, o + 64 * F_ + 192, 0);
    store_half(p2, o + 64 * F_ + 192, 1);
}

typedef CUresult (*EncodeTiledFn)(CUtensorMap*, CUtensorMapDataType, cuuint32_t, void*, const cuuint64_t*, const cuuint64_t*, const cuuint32_t*, const cuuint32_t*, CUtensorMapInterleave, CUtensorMapSwizzle, CUtensorMapL2promotion, CUtensorMapFloatOOBfill);

extern "C" void kernel_launch(void* const* d_in, const int* in_sizes, int n_in, void* d_out, int out_size) {
    static EncodeTiledFn enc = nullptr;
    static decltype(&fused_kernel<true>) kern = nullptr;
    static void *p_w = nullptr, *p_flags = nullptr, *p_prof = nullptr;
    if (!enc) {
        void* fn = nullptr; cudaDriverEntryPointQueryResult qr;
        cudaGetDriverEntryPoint("cuTensorMapEncodeTiled", &fn, cudaEnableDefault, &qr);
        enc = (EncodeTiledFn)fn;
        int dev = 0, rsv = 0;
        cudaGetDevice(&dev);
        cudaDeviceGetAttribute(&rsv, cudaDevAttrReservedSharedMemoryPerBlock, dev);
        kern = rsv == 1024 && !NOHARD ? fused_kernel<true> : fused_kernel<false>;
        cudaFuncSetAttribute(kern, cudaFuncAttributeMaxDynamicSharedMemorySize, SMEM_BYTES);
        cudaGetSymbolAddress(&p_w, g_w);
        cudaGetSymbolAddress(&p_flags, g_flags);
    }
    CUtensorMap tmx, tmx64, tmq;
    {
        cuuint64_t gdim[2] = {(cuuint64_t)F_, (cuuint64_t)D_};
        cuuint64_t gstr[1] = {(cuuint64_t)F_ * 4};
        cuuint32_t box[2] = {(cuuint32_t)BN, 16};
        cuuint32_t estr[2] = {1, 1};
        enc(&tmq, CU_TENSOR_MAP_DATA_TYPE_INT32, 2, d_in[1], gdim, gstr, box, estr, CU_TENSOR_MAP_INTERLEAVE_NONE,
            CU_TENSOR_MAP_SWIZZLE_NONE, CU_TENSOR_MAP_L2_PROMOTION_L2_128B, CU_TENSOR_MAP_FLOAT_OOB_FILL_NONE);
    }
    {
        cuuint64_t gdim[2] = {(cuuint64_t)D_, (cuuint64_t)S_};
        cuuint64_t gstr[1] = {(cuuint64_t)D_ * 2};
        cuuint32_t box[2] = {(cuuint32_t)BK, (cuuint32_t)BM};
        cuuint32_t estr[2] = {1, 1};
        enc(&tmx, CU_TENSOR_MAP_DATA_TYPE_BFLOAT16, 2, d_in[0], gdim, gstr, box, estr, CU_TENSOR_MAP_INTERLEAVE_NONE,
            CU_TENSOR_MAP_SWIZZLE_128B, CU_TENSOR_MAP_L2_PROMOTION_L2_128B, CU_TENSOR_MAP_FLOAT_OOB_FILL_NONE);
        box[1] = 64;
        enc(&tmx64, CU_TENSOR_MAP_DATA_TYPE_BFLOAT16, 2, d_in[0], gdim, gstr, box, estr, CU_TENSOR_MAP_INTERLEAVE_NONE,
            CU_TENSOR_MAP_SWIZZLE_128B, CU_TENSOR_MAP_L2_PROMOTION_L2_128B, CU_TENSOR_MAP_FLOAT_OOB_FILL_NONE);
    }
    kern<<<128, 256, SMEM_BYTES>>>((const int*)d_in[1], (const unsigned short*)d_in[2], (__nv_bfloat16*)d_out, (uint4*)p_w, (unsigned*)p_flags, tmq, tmx64, tmx
    );
    (void)p_prof;
}
```

```cpp
#include <cuda_runtime.h>
#include <cuda_bf16.h>
#include <cuda.h>
#include <stdint.h>
#include <stdio.h>

#define PR1 1200
#define PX0 1000
#define PX0B 2600
#define PR2 1900
#define W1D 150
#define W2D 400
#define W3D 600
#define R1E 1
#define X1E 2900
#define MAP 1
#define PFM 4
#define PFW 8
#define PFE 0
#define NOW 2
#define PSL 0
#define PSL2 0
#define R3A 3
#define R2A 1
#define R4A 0
#define W4L2 0
#define CSP 10
#define PSTA 110
#define PSF 3
#define L11 3
#define L12 7
#define DSP 5
#define PSB0 150
#define PSTB 110
#define PSTD 100

#define NOHARD 0

constexpr int S_ = 2048, D_ = 1024, F_ = 3584;
constexpr int BM = 256, BN = 224, BK = 64;
constexpr int X_BYTES = BM * BK * 2;
constexpr int W_BYTES = BN * BK * 2;
constexpr int CHUNK_BYTES = BN * 16;
constexpr int SLAB_BYTES = 16 * BN * 4;
constexpr int OFF_X = 0;
constexpr int OFF_W = 3 * X_BYTES;
constexpr int OFF_STG = OFF_W + 3 * W_BYTES;
constexpr int OFF_LUT = OFF_W + 4 * W_BYTES;
constexpr int OFF_BAR = OFF_LUT + 7 * 2048;
constexpr int OFF_PROF = OFF_BAR + 1024;
constexpr int SMEM_BYTES = OFF_PROF + 1024 + 1024;
constexpr int OFF_SLAB0 = OFF_W + 2 * W_BYTES, OFF_SLAB2 = OFF_X + 2 * X_BYTES;
constexpr int B_FULL = 0;
constexpr int B_XV = 12;
constexpr int B_WF = 17;
constexpr int B_EMPTY = 22;
constexpr int B_X0B = 34;
constexpr int B_X15 = 35;
constexpr int B_DQ = 34;
constexpr int B_SLAB = 42;
constexpr int B_LUT = 46;
constexpr int NFAST = 4;
constexpr unsigned long long R_BATCH = 0x60050400ull, W_FLAG = 0x600504000ull;
constexpr unsigned L1_MASK = W4L2 ? 0x2A : 0x2E, L2_MASK = W4L2 ? 0x1EA : 0x1E8;

__device__ __align__(1024) uint4 g_w[(size_t)F_ * D_ / 8];
__device__ __align__(128) unsigned g_flags[16 * 32];

__device__ __forceinline__ uint32_t smem_u32(const void* p) { return (uint32_t)__cvta_generic_to_shared(p); }
__device__ __forceinline__ void mbar_init(uint32_t bar, uint32_t cnt) { asm volatile("mbarrier.init.shared::cta.b64 [%0], %1;" ::"r"(bar), "r"(cnt) : "memory"); }
__device__ __forceinline__ void mbar_wait(uint32_t bar) {
    asm volatile("{\n.reg .pred p;\nWAIT_LOOP:\nmbarrier.try_wait.parity.shared::cta.b64 p, [%0], 0;\n@p bra WAIT_DONE;\nbra WAIT_LOOP;\nWAIT_DONE:\n}" ::"r"(bar) : "memory");
}
__device__ __forceinline__ void e_arrive(uint32_t bar) {
    asm volatile("{\n.reg .pred p;\nelect.sync _|p, 0xffffffff;\n@p mbarrier.arrive.shared::cta.b64 _, [%0];\n}" ::"r"(bar) : "memory");
}
__device__ __forceinline__ void e_expect(uint32_t bar, uint32_t bytes) {
    asm volatile("{\n.reg .pred p;\nelect.sync _|p, 0xffffffff;\n@p mbarrier.arrive.expect_tx.shared::cta.b64 _, [%0], %1;\n}" ::"r"(bar), "r"(bytes) : "memory");
}
__device__ __forceinline__ void e_tma(uint32_t bar, const CUtensorMap* tm, uint32_t d0, int x0, int y0) {
    asm volatile("{\n.reg .pred p;\nelect.sync _|p, 0xffffffff;\n"
                 "@p cp.async.bulk.tensor.2d.shared::cluster.global.mbarrier::complete_tx::bytes [%2], [%1, {%3, %4}], [%0];\n}"
                 ::"r"(bar), "l"(tm), "r"(d0), "r"(x0), "r"(y0) : "memory");
}
__device__ __forceinline__ void e_bulk(uint32_t bar, uint32_t bytes, uint32_t dst, const void* src) {
    asm volatile("{\n.reg .pred p;\nelect.sync _|p, 0xffffffff;\n"
                 "@p mbarrier.arrive.expect_tx.shared::cta.b64 _, [%0], %1;\n"
                 "@p cp.async.bulk.shared::cluster.global.mbarrier::complete_tx::bytes [%2], [%3], %1, [%0];\n}"
                 ::"r"(bar), "r"(bytes), "r"(dst), "l"(src) : "memory");
}
__device__ __forceinline__ void e_bulk_p(uint32_t on, uint32_t bar, uint32_t bytes, uint32_t dst, const void* src) {
    if (on) asm volatile("{\n.reg .pred p;\nelect.sync _|p, 0xffffffff;\n"
                         "@p cp.async.bulk.shared::cluster.global.mbarrier::complete_tx::bytes [%2], [%3], %1, [%0];\n}"
                         ::"r"(bar), "r"(bytes), "r"(dst), "l"(src) : "memory");
}
__device__ __forceinline__ void e_publish(unsigned* flag) {
    asm volatile("{\n.reg .pred p;\nelect.sync _|p, 0xffffffff;\n@p red.release.gpu.global.add.u32 [%0], 1;\n}" ::"l"(flag) : "memory");
}
__device__ __forceinline__ unsigned ld_flag(const unsigned* f) { unsigned v; asm volatile("ld.relaxed.gpu.global.u32 %0, [%1];" : "=r"(v) : "l"(f) : "memory"); return v; }
__device__ __forceinline__ void finish_poll(const unsigned* f, unsigned v, unsigned target) {
    int n = 0;
    while (!__all_sync(0xffffffff, (int)(v - target) >= 0) && ++n < 4000000) v = ld_flag(f);
    asm volatile("fence.acquire.gpu;" ::: "memory");
    asm volatile("fence.proxy.async.global;" ::: "memory");
}
template <typename T> __device__ __forceinline__ T* ptr_add(T* base, uint32_t off) {
    uint64_t r;
    asm("{\n.reg .u32 l, h;\nmov.b64 {l, h}, %1;\nadd.cc.u32 l, l, %2;\naddc.u32 h, h, 0;\nmov.b64 %0, {l, h};\n}" : "=l"(r) : "l"(base), "r"(off));
    return (T*)r;
}
__device__ __forceinline__ void wgmma_fence() { asm volatile("wgmma.fence.sync.aligned;" ::: "memory"); }
__device__ __forceinline__ void wgmma_commit() { asm volatile("wgmma.commit_group.sync.aligned;" ::: "memory"); }
template <int N> __device__ __forceinline__ void wgmma_wait() { asm volatile("wgmma.wait_group.sync.aligned %0;" ::"n"(N) : "memory"); }
__device__ __forceinline__ void wgmma_m64n224k16(float (&d)[112], uint64_t da, uint64_t db, int scale_d) {
    asm volatile(
        "{\n.reg .pred p;\nsetp.ne.b32 p, %114, 0;\n"
        "wgmma.mma_async.sync.aligned.m64n224k16.f32.bf16.bf16 "
        "{%0, %1, %2, %3, %4, %5, %6, %7, %8, %9, %10, %11, %12, %13, %14, %15, "
        "%16, %17, %18, %19, %20, %21, %22, %23, %24, %25, %26, %27, %28, %29, %30, %31, "
        "%32, %33, %34, %35, %36, %37, %38, %39, %40, %41, %42, %43, %44, %45, %46, %47, "
        "%48, %49, %50, %51, %52, %53, %54, %55, %56, %57, %58, %59, %60, %61, %62, %63, "
        "%64, %65, %66, %67, %68, %69, %70, %71, %72, %73, %74, %75, %76, %77, %78, %79, "
        "%80, %81, %82, %83, %84, %85, %86, %87, %88, %89, %90, %91, %92, %93, %94, %95, "
        "%96, %97, %98, %99, %100, %101, %102, %103, %104, %105, %106, %107, %108, %109, %110, %111}, "
        "%112, %113, p, 1, 1, 0, 0;\n}\n"
        : "+f"(d[0]), "+f"(d[1]), "+f"(d[2]), "+f"(d[3]), "+f"(d[4]), "+f"(d[5]), "+f"(d[6]), "+f"(d[7]),
          "+f"(d[8]), "+f"(d[9]), "+f"(d[10]), "+f"(d[11]), "+f"(d[12]), "+f"(d[13]), "+f"(d[14]), "+f"(d[15]),
          "+f"(d[16]), "+f"(d[17]), "+f"(d[18]), "+f"(d[19]), "+f"(d[20]), "+f"(d[21]), "+f"(d[22]), "+f"(d[23]),
          "+f"(d[24]), "+f"(d[25]), "+f"(d[26]), "+f"(d[27]), "+f"(d[28]), "+f"(d[29]), "+f"(d[30]), "+f"(d[31]),
          "+f"(d[32]), "+f"(d[33]), "+f"(d[34]), "+f"(d[35]), "+f"(d[36]), "+f"(d[37]), "+f"(d[38]), "+f"(d[39]),
          "+f"(d[40]), "+f"(d[41]), "+f"(d[42]), "+f"(d[43]), "+f"(d[44]), "+f"(d[45]), "+f"(d[46]), "+f"(d[47]),
          "+f"(d[48]), "+f"(d[49]), "+f"(d[50]), "+f"(d[51]), "+f"(d[52]), "+f"(d[53]), "+f"(d[54]), "+f"(d[55]),
          "+f"(d[56]), "+f"(d[57]), "+f"(d[58]), "+f"(d[59]), "+f"(d[60]), "+f"(d[61]), "+f"(d[62]), "+f"(d[63]),
          "+f"(d[64]), "+f"(d[65]), "+f"(d[66]), "+f"(d[67]), "+f"(d[68]), "+f"(d[69]), "+f"(d[70]), "+f"(d[71]),
          "+f"(d[72]), "+f"(d[73]), "+f"(d[74]), "+f"(d[75]), "+f"(d[76]), "+f"(d[77]), "+f"(d[78]), "+f"(d[79]),
          "+f"(d[80]), "+f"(d[81]), "+f"(d[82]), "+f"(d[83]), "+f"(d[84]), "+f"(d[85]), "+f"(d[86]), "+f"(d[87]),
          "+f"(d[88]), "+f"(d[89]), "+f"(d[90]), "+f"(d[91]), "+f"(d[92]), "+f"(d[93]), "+f"(d[94]), "+f"(d[95]),
          "+f"(d[96]), "+f"(d[97]), "+f"(d[98]), "+f"(d[99]), "+f"(d[100]), "+f"(d[101]), "+f"(d[102]), "+f"(d[103]),
          "+f"(d[104]), "+f"(d[105]), "+f"(d[106]), "+f"(d[107]), "+f"(d[108]), "+f"(d[109]), "+f"(d[110]), "+f"(d[111])
        : "l"(da), "l"(db), "r"(scale_d));
}

__device__ __forceinline__ void wgmma_rs(float (&d)[16], const uint32_t* a, uint64_t db) {
    asm volatile("wgmma.mma_async.sync.aligned.m64n32k16.f32.bf16.bf16 {%0, %1, %2, %3, %4, %5, %6, %7, %8, %9, %10, %11, %12, %13, %14, %15}, {%16, %17, %18, %19}, %20, 1, 1, 1, 0;"
        : "+f"(d[0]), "+f"(d[1]), "+f"(d[2]), "+f"(d[3]), "+f"(d[4]), "+f"(d[5]), "+f"(d[6]), "+f"(d[7]), "+f"(d[8]), "+f"(d[9]), "+f"(d[10]), "+f"(d[11]), "+f"(d[12]), "+f"(d[13]), "+f"(d[14]), "+f"(d[15])
        : "r"(a[0]), "r"(a[1]), "r"(a[2]), "r"(a[3]), "l"(db));
}
__device__ __forceinline__ void wgmma_rs(float (&d)[32], const uint32_t* a, uint64_t db) {
    asm volatile("wgmma.mma_async.sync.aligned.m64n64k16.f32.bf16.bf16 {%0, %1, %2, %3, %4, %5, %6, %7, %8, %9, %10, %11, %12, %13, %14, %15, %16, %17, %18, %19, %20, %21, %22, %23, %24, %25, %26, %27, %28, %29, %30, %31}, {%32, %33, %34, %35}, %36, 1, 1, 1, 0;"
        : "+f"(d[0]), "+f"(d[1]), "+f"(d[2]), "+f"(d[3]), "+f"(d[4]), "+f"(d[5]), "+f"(d[6]), "+f"(d[7]), "+f"(d[8]), "+f"(d[9]), "+f"(d[10]), "+f"(d[11]), "+f"(d[12]), "+f"(d[13]), "+f"(d[14]), "+f"(d[15]), "+f"(d[16]), "+f"(d[17]), "+f"(d[18]), "+f"(d[19]), "+f"(d[20]), "+f"(d[21]), "+f"(d[22]), "+f"(d[23]), "+f"(d[24]), "+f"(d[25]), "+f"(d[26]), "+f"(d[27]), "+f"(d[28]), "+f"(d[29]), "+f"(d[30]), "+f"(d[31])
        : "r"(a[0]), "r"(a[1]), "r"(a[2]), "r"(a[3]), "l"(db));
}
__device__ __forceinline__ void wgmma_rs(float (&d)[64], const uint32_t* a, uint64_t db) {
    asm volatile("wgmma.mma_async.sync.aligned.m64n128k16.f32.bf16.bf16 {%0, %1, %2, %3, %4, %5, %6, %7, %8, %9, %10, %11, %12, %13, %14, %15, %16, %17, %18, %19, %20, %21, %22, %23, %24, %25, %26, %27, %28, %29, %30, %31, %32, %33, %34, %35, %36, %37, %38, %39, %40, %41, %42, %43, %44, %45, %46, %47, %48, %49, %50, %51, %52, %53, %54, %55, %56, %57, %58, %59, %60, %61, %62, %63}, {%64, %65, %66, %67}, %68, 1, 1, 1, 0;"
        : "+f"(d[0]), "+f"(d[1]), "+f"(d[2]), "+f"(d[3]), "+f"(d[4]), "+f"(d[5]), "+f"(d[6]), "+f"(d[7]), "+f"(d[8]), "+f"(d[9]), "+f"(d[10]), "+f"(d[11]), "+f"(d[12]), "+f"(d[13]), "+f"(d[14]), "+f"(d[15]), "+f"(d[16]), "+f"(d[17]), "+f"(d[18]), "+f"(d[19]), "+f"(d[20]), "+f"(d[21]), "+f"(d[22]), "+f"(d[23]), "+f"(d[24]), "+f"(d[25]), "+f"(d[26]), "+f"(d[27]), "+f"(d[28]), "+f"(d[29]), "+f"(d[30]), "+f"(d[31]), "+f"(d[32]), "+f"(d[33]), "+f"(d[34]), "+f"(d[35]), "+f"(d[36]), "+f"(d[37]), "+f"(d[38]), "+f"(d[39]), "+f"(d[40]), "+f"(d[41]), "+f"(d[42]), "+f"(d[43]), "+f"(d[44]), "+f"(d[45]), "+f"(d[46]), "+f"(d[47]), "+f"(d[48]), "+f"(d[49]), "+f"(d[50]), "+f"(d[51]), "+f"(d[52]), "+f"(d[53]), "+f"(d[54]), "+f"(d[55]), "+f"(d[56]), "+f"(d[57]), "+f"(d[58]), "+f"(d[59]), "+f"(d[60]), "+f"(d[61]), "+f"(d[62]), "+f"(d[63])
        : "r"(a[0]), "r"(a[1]), "r"(a[2]), "r"(a[3]), "l"(db));
}

__device__ __forceinline__ uint32_t pack_bf16(float lo, float hi) {
    uint32_t r; asm("cvt.rn.bf16x2.f32 %0, %1, %2;" : "=r"(r) : "f"(hi), "f"(lo)); return r;
}
__device__ __forceinline__ uint32_t lds32(uint32_t a) { uint32_t v; asm volatile("ld.shared.b32 %0, [%1];" : "=r"(v) : "r"(a)); return v; }
__device__ __forceinline__ void sts32(uint32_t a, uint32_t v) { asm volatile("st.shared.b32 [%0], %1;" ::"r"(a), "r"(v) : "memory"); }
__device__ __forceinline__ void sts128(uint32_t a, uint4 v) { asm volatile("st.shared.v4.b32 [%0], {%1,%2,%3,%4};" ::"r"(a), "r"(v.x), "r"(v.y), "r"(v.z), "r"(v.w) : "memory"); }
__device__ __forceinline__ void stg128(void* p, uint4 v) { asm volatile("st.global.v4.b32 [%0], {%1,%2,%3,%4};" ::"l"(p), "r"(v.x), "r"(v.y), "r"(v.z), "r"(v.w) : "memory"); }
__device__ __forceinline__ void cp16(uint32_t dst, const void* src) { asm volatile("cp.async.cg.shared.global [%0], [%1], 16;" ::"r"(dst), "l"(src) : "memory"); }
__device__ __forceinline__ void cp_commit() { asm volatile("cp.async.commit_group;" ::: "memory"); }
template <int N> __device__ __forceinline__ void cp_wait() { asm volatile("cp.async.wait_group %0;" ::"n"(N) : "memory"); }
__device__ __forceinline__ uint4 dequant8(uint32_t raw, uint32_t lut_a) {
    uint32_t v[8];
#pragma unroll
    for (int i = 0; i < 8; i++) v[i] = lds32(raw + i * 128);
#pragma unroll
    for (int i = 0; i < 8; i++) v[i] = lds32(lut_a + v[i] * 128);
    uint4 o;
    o.x = __byte_perm(v[0], v[1], 0x5410); o.y = __byte_perm(v[2], v[3], 0x5410);
    o.z = __byte_perm(v[4], v[5], 0x5410); o.w = __byte_perm(v[6], v[7], 0x5410);
    return o;
}
__device__ __forceinline__ uint32_t prmt(uint32_t a, uint32_t b, uint32_t c) { uint32_t r; asm("prmt.b32 %0, %1, %2, %3;" : "=r"(r) : "r"(a), "r"(b), "r"(c)); return r; }
__device__ __forceinline__ uint4 lookup8_reg(const uint32_t* c, const uint32_t (&T)[8]) {
    uint32_t o[4];
#pragma unroll
    for (int h = 0; h < 2; h++) {
        const uint32_t sel = c[4 * h] + c[4 * h + 1] * 16 + c[4 * h + 2] * 256 + c[4 * h + 3] * 4096;
        const uint32_t s7 = sel & 0x7777u;
        uint32_t m;
        asm("lop3.b32 %0, %1, %2, 0x3210, 0xEA;" : "=r"(m) : "r"(sel >> 1), "r"(0x4444u));
        const uint32_t lo = prmt(prmt(T[0], T[1], s7), prmt(T[2], T[3], s7), m);
        const uint32_t hi = prmt(prmt(T[4], T[5], s7), prmt(T[6], T[7], s7), m);
        o[2 * h] = prmt(lo, hi, 0x5140u); o[2 * h + 1] = prmt(lo, hi, 0x7362u);
    }
    return make_uint4(o[0], o[1], o[2], o[3]);
}
template <int N>
__device__ __forceinline__ void pack_half(const float (&acc)[N], int H, uint32_t* r) {
    const int b = (H >> 1) * 16 + (H & 1) * 2;
#pragma unroll
    for (int i = 0; i < 4; i++) asm volatile("cvt.rn.bf16x2.f32 %0, %1, %2;" : "=r"(r[i]) : "f"(acc[b + 4 * i + 1]), "f"(acc[b + 4 * i]));
}
__device__ __forceinline__ void store_packed(__nv_bfloat16* o, int H, const uint32_t* r, int on = 1) {
    asm volatile("{\n.reg .pred p;\nsetp.ne.b32 p, %5, 0;\n@p st.global.v4.b32 [%0], {%1,%2,%3,%4};\n}"
                 ::"l"(o + (H & 1) * 8 * F_ + (H >> 1) * 32), "r"(r[0]), "r"(r[1]), "r"(r[2]), "r"(r[3]), "r"(on) : "memory");
}
template <int N>
__device__ __forceinline__ void store_half(const float (&acc)[N], __nv_bfloat16* o, int H, int on = 1) {
    const int b = (H >> 1) * 16 + (H & 1) * 2;
    const uint32_t r[4] = {pack_bf16(acc[b], acc[b + 1]), pack_bf16(acc[b + 4], acc[b + 5]), pack_bf16(acc[b + 8], acc[b + 9]), pack_bf16(acc[b + 12], acc[b + 13])};
    store_packed(o, H, r, on);
}
__device__ __forceinline__ unsigned clk() { unsigned c; asm volatile("mov.u32 %0, %%clock;" : "=r"(c)); return c; }
__device__ __forceinline__ void wait_until(unsigned t0, unsigned dt) { while (clk() - t0 < dt) {} }

#define TSK(w, i)
#define TS8(i)
#define TSW(w, i)
#define TS9(i)

template <bool HARD>
__global__ void __launch_bounds__(256, 1)
fused_kernel(const int* __restrict__ qw, const unsigned short* __restrict__ lut, __nv_bfloat16* __restrict__ out,
             uint4* __restrict__ wscr, unsigned* __restrict__ flags,
             const __grid_constant__ CUtensorMap tmq, const __grid_constant__ CUtensorMap tmx64, const __grid_constant__ CUtensorMap tmx
) {
    extern __shared__ uint8_t smem_raw[];
    const uint32_t sbase = HARD ? 1024u : (smem_u32(smem_raw) + 1023) & ~1023u;
    const uint32_t bars = sbase + OFF_BAR;
    const int tid = threadIdx.x, lane = tid & 31;
    const int mt = (blockIdx.x >> 6) * 4 + (blockIdx.x & 3), g = ((blockIdx.x >> 3) & 7) * 2 + ((blockIdx.x >> 2) & 1);
    const unsigned clk0 = clk();
    const int warp = __shfl_sync(0xffffffff, tid >> 5, 0);
    if (tid >= 224) {
        asm volatile("{\n.reg .pred p;\nelect.sync _|p, 0xffffffff;\n"
                     "@p mbarrier.init.shared::cta.b64 [%0], 1;\n"
                     "@p fence.mbarrier_init.release.cluster;\n"
                     "@p mbarrier.arrive.expect_tx.shared::cta.b64 _, [%0], %1;\n"
                     "@p cp.async.bulk.tensor.2d.shared::cluster.global.mbarrier::complete_tx::bytes [%3], [%2, {%4, 0}], [%0];\n}"
                     ::"r"(bars + 8 * B_SLAB), "n"(SLAB_BYTES), "l"(&tmq), "r"(sbase + OFF_SLAB0), "r"(g * BN) : "memory");
    } else {
        const unsigned short* lp = ptr_add(lut, ((lane >> 2) * F_ + g * BN + (tid & ~31) + (lane & 3) * 8) * 2);
        asm volatile("cp.async.cg.shared.global [%0], [%1], 16;\ncp.async.cg.shared.global [%0+512], [%1+57344], 16;\ncp.async.commit_group;"
                     ::"r"(sbase + OFF_STG + (tid >> 5) * 4096 + lane * 16), "l"(lp) : "memory");
    }
    const int sl = warp - 3;
    auto load_slab = [&]() {
        e_tma(bars + 8 * (B_SLAB + sl), &tmq, sbase + (sl < 2 ? OFF_SLAB0 : OFF_SLAB2 - 2 * SLAB_BYTES) + sl * SLAB_BYTES, g * BN, sl * 16);
    };
    if (warp >= 4 && warp < 7) {
        asm volatile("{\n.reg .pred p;\nelect.sync _|p, 0xffffffff;\n"
                     "@p mbarrier.init.shared::cta.b64 [%0], 1;\n"
                     "@p fence.mbarrier_init.release.cluster;\n"
                     "@p mbarrier.arrive.expect_tx.shared::cta.b64 _, [%0], %1;\n}"
                     ::"r"(bars + 8 * (B_SLAB + sl)), "n"(SLAB_BYTES) : "memory");
        if (sl < NOW) load_slab();
    } else if (warp < 2) {
        asm volatile("{\n.reg .pred p;\nelect.sync _|p, 0xffffffff;\n"
                     "@p mbarrier.init.shared::cta.b64 [%0], %1;\n"
                     "@p fence.mbarrier_init.release.cluster;\n}" ::"r"(bars + 8 * (warp ? B_LUT : B_FULL)), "r"(8 - warp) : "memory");
    }
    asm volatile("bar.sync 1, 256;" ::: "memory");
    const int wg = warp >> 2;

    const int fl = 8 * ((lane & 7) >> 1) + 2 * (lane >> 3) + (lane & 1);
    const uint32_t lut_a = sbase + OFF_LUT + warp * 2048 + lane * 4;
    const uint32_t stg = sbase + OFF_STG + warp * 4096;
    unsigned* myflags = flags + g * 32;
    const uint4* wgrp = wscr + (size_t)g * 128 * BN;
    unsigned target = 0;

    auto issue_x = [&](int s, int slot) {
        e_tma(bars + 8 * (B_FULL + s), &tmx, sbase + OFF_X + slot * X_BYTES, s * BK, mt * BM);
    };
    auto pf_x = [&](int s) {
        asm volatile("{\n.reg .pred p;\nelect.sync _|p, 0xffffffff;\n@p cp.async.bulk.prefetch.tensor.2d.L2.global [%0, {%1, %2}];\n}"
                     ::"l"(&tmx64), "r"((s + (g >> 2)) * BK), "r"(mt * BM + (g & 3) * 64) : "memory");
    };
    auto issue_xv = [&](int v, int w, uint32_t bar) {
        const uint32_t dst = sbase + OFF_X + (v & 1) * X_BYTES + w * 16384;
        const int k0 = (12 + 2 * (v & 1)) * BK, r0 = mt * BM + w * 128 + ((v >> 1) & 1) * 64;
        e_tma(bar, &tmx64, dst, k0, r0);
        e_tma(bar, &tmx64, dst + 8192, k0 + BK, r0);
    };
    auto issue_w = [&](int s, int slot, int bar) {
        e_bulk(bars + 8 * bar, W_BYTES, sbase + OFF_W + slot * W_BYTES, wgrp + s * 8 * BN);
    };
    auto load_blk = [&](int t, int c) {
        const int* src = ptr_add(qw, (uint32_t)(((t * BK + mt * 8 + (lane >> 3)) * F_ + g * BN + c * 32 + (lane & 7) * 4) * 4));
        asm volatile("cp.async.cg.shared.global [%0], [%1], 16;\ncp.async.cg.shared.global [%0+512], [%1+57344], 16;"
                     ::"r"(sbase + OFF_STG + c * 4096 + (t & 3) * 1024 + lane * 16), "l"(src) : "memory");
    };
    auto load_raw = [&](int t) { if (t < 16) load_blk(t, warp); cp_commit(); };
    auto unit = [&](int t, int c) { return ptr_add(wscr, (uint32_t)(((g * 128 + t * 8 + mt) * BN + c * 32 + lane) * 16)); };
    auto foreign2 = [&]() {
        const int c = warp - 4;
        stg128(unit(2, c), dequant8(sbase + OFF_STG + c * 4096 + 2 * 1024 + fl * 4, sbase + OFF_LUT + c * 2048 + lane * 4));
    };
    auto coop = [&](int t) {
        cp_wait<1>();
        __syncwarp();
        load_raw(t + 2);
        stg128(unit(t, warp), dequant8(stg + (t & 3) * 1024 + fl * 4, lut_a));
    };

    if (warp == 7) {
        if (lane == 0) {
            asm volatile("prefetch.tensormap [%0];" ::"l"(&tmx) : "memory");
            asm volatile("prefetch.tensormap [%0];" ::"l"(&tmx64) : "memory");
        }
        __syncwarp();
        auto x0 = [&](int w, uint32_t bar) {
            e_expect(bar, X_BYTES / 2);
            e_tma(bar, &tmx64, sbase + OFF_X + w * 16384, 0, mt * BM + w * 128);
            e_tma(bar, &tmx64, sbase + OFF_X + w * 16384 + 8192, 0, mt * BM + w * 128 + 64);
        };
        wait_until(clk0, PX0);
        x0(0, bars + 8 * B_FULL);
        target = ld_flag(myflags + 6);
        wait_until(clk0, PR2);
        load_blk(2, 3);
        cp_commit();
        mbar_wait(bars + 8 * B_LUT);
        wait_until(clk0, PX0B);
        x0(1, bars + 8 * B_X0B);
        target = (target | 7) + 1;
        if (X1E) wait_until(clk0, X1E); else mbar_wait(bars + 8 * B_FULL);
        issue_x(1, 1);
        cp_wait<0>();
        __syncwarp();
        foreign2();
        TSW(7, 3);
    } else {
        if (wg == 1 && sl >= NOW) { if (PSL) wait_until(clk0, PSL + (sl - 2) * PSL2); load_slab(); }
        if (lane == 0) {
#pragma unroll
            for (int i = 0; i < 6; i++) {
                const int b = 1 + warp * 6 + i;
                if (b < B_SLAB) mbar_init(bars + 8 * b, b < B_DQ + 4 ? 1 : 7);
                if (b < B_XV) asm volatile("mbarrier.arrive.expect_tx.shared::cta.b64 _, [%0], %1;" ::"r"(bars + 8 * b), "r"(X_BYTES + W_BYTES) : "memory");
            }
            asm volatile("fence.mbarrier_init.release.cluster;" ::: "memory");
        }
        __syncwarp();
        wait_until(clk0, PR1);
        load_raw(1);
        uint32_t lv[16], v[32], T[8];
        cp_wait<1>();
        __syncwarp();
#pragma unroll
        for (int i = 0; i < 16; i++) asm volatile("ld.shared.u16 %0, [%1];" : "=r"(lv[i]) : "r"(stg + i * 64 + fl * 2));
#pragma unroll
        for (int i = 0; i < 16; i++) lv[i] = lv[i] ? lv[i] : 0x8000u;
#pragma unroll
        for (int i = 0; i < 4; i++) {
            const uint32_t p01 = prmt(lv[4 * i], lv[4 * i + 1], 0x5140u), p23 = prmt(lv[4 * i + 2], lv[4 * i + 3], 0x5140u);
            T[i] = prmt(p01, p23, 0x5410u); T[4 + i] = prmt(p01, p23, 0x7632u);
        }
        TSW(0, 7);
#pragma unroll
        for (int i = 0; i < 16; i++) sts32(lut_a + i * 128, lv[i]);
        __syncwarp();
        e_arrive(bars + 8 * B_LUT);
        auto own_task = [&](int t) {
            __syncwarp();
            uint32_t c[8];
#pragma unroll
            for (int i = 0; i < 8; i++) c[i] = lds32(stg + t * 1024 + fl * 4 + i * 128);
            stg128(unit(t, warp), lookup8_reg(c, T));
        };
        auto piece_ld = [&](int j) {
            mbar_wait(bars + 8 * (B_SLAB + j));
#pragma unroll
            for (int i = 0; i < 16; i++) v[(j & 1) * 16 + i] = lds32(sbase + (j < 2 ? OFF_SLAB0 : OFF_SLAB2) + (j & 1) * SLAB_BYTES + i * (BN * 4) + (warp * 32 + fl) * 4);
        };
        auto piece_st = [&](int j) {
            const uint32_t dst = sbase + OFF_W + j * 2 * CHUNK_BYTES + (warp * 32 + lane) * 16;
            sts128(dst, lookup8_reg(v + (j & 1) * 16, T));
            sts128(dst + CHUNK_BYTES, lookup8_reg(v + (j & 1) * 16 + 8, T));
            TSW(0, 8 + j);
        };
        if (R2A == 0 && wg == 1) { load_blk(2, warp); load_blk(2, warp - 4); cp_commit(); }
        piece_ld(0);
        if (R2A == 1 && wg == 1) { load_blk(2, warp); load_blk(2, warp - 4); cp_commit(); }
        piece_st(0);
        if (R2A == 2 && wg == 1) { load_blk(2, warp); load_blk(2, warp - 4); cp_commit(); }
        piece_ld(1);
        piece_ld(2);
        if (R3A == 2 && wg == 0) load_raw(3);
        piece_st(1);
        piece_ld(3);
        if (R3A == 3 && wg == 0) load_raw(3);
        if (R1E == 2) { if (wg == 0) cp_wait<1>(); else cp_wait<1>(); own_task(1); }
        piece_st(2);
        if (R1E == 1) { cp_wait<1>(); own_task(1); }
        piece_st(3);
        asm volatile("fence.proxy.async.shared::cta;" ::: "memory");
        __syncwarp();
        e_arrive(bars + 8 * B_FULL);
        if (!R1E) { if (R3A == 4 && wg == 0) cp_wait<0>(); else cp_wait<1>(); own_task(1); }
        if (R3A == 4 && wg == 0) load_raw(3);
        TSW(0, 14);
        if (wg == 1) {
            load_raw(3);
            cp_wait<1>();
            own_task(2);
            if (R4A == 0) load_raw(4);
            mbar_wait(bars + 8 * B_LUT);
            foreign2();
            if (R4A == 1) load_raw(4);
        }
        TSW(4, 12);
    }

    float acc0[112], acc1[112];
    const uint64_t descA_hi = ((uint64_t)1 << 62) | ((uint64_t)(1024 >> 4) << 32) | ((uint64_t)1 << 16);
    const uint64_t descB_hi = ((uint64_t)(128 >> 4) << 32) | ((uint64_t)(CHUNK_BYTES >> 4) << 16);
    const uint32_t a16 = ((sbase & 0x3FFFF) >> 4) + wg * 1024 + (uint32_t)descA_hi, b16w = (((sbase + OFF_W) & 0x3FFFF) >> 4) + (uint32_t)descB_hi;
    auto dscA = [&](uint32_t lo) { return (descA_hi & 0xFFFFFFFF00000000ull) | lo; };
    auto dscB = [&](uint32_t lo) { return (descB_hi & 0xFFFFFFFF00000000ull) | lo; };
    uint32_t xo = 0, wo = 0, wo_prev = 2 * W_BYTES;
    const uint4* wnext = wgrp + 2 * 8 * BN;
    auto validate = [&](int t) {
        const uint32_t a = sbase + OFF_W + wo;
        for (int n = 0; n < 2000000; n++) {
            uint32_t m = 0xffffffffu;
#pragma unroll
            for (int i = 0; i < 7; i++) m = min(m, lds32(a + tid * 32 + (lane >> 2) * 4 + i * 4096));
            if (__all_sync(0xffffffff, m != 0)) break;
            const uint4* src = ptr_add(wgrp, (uint32_t)((t * 8 * BN + warp * 64 + lane) * 16));
#pragma unroll 1
            for (int i = 0; i < 14; i++) cp16(a + (warp * 64 + lane + (i >> 1) * 256 + (i & 1) * 32) * 16, src + (i >> 1) * 256 + (i & 1) * 32);
            cp_commit();
            cp_wait<0>();
            asm volatile("fence.proxy.async.shared::cta;" ::: "memory");
            __syncwarp();
        }
    };
    auto batch = [&](int s, bool in_loop) {
        mbar_wait(bars + 8 * (B_FULL + s));
        if (!in_loop && s == 0 && wg == 1) mbar_wait(bars + 8 * B_X0B);
        if (in_loop && wg == 0 && s <= NFAST) validate(s);
        if (s + wg > 0) asm volatile("bar.sync %0, 256;" ::"r"(2 + wg) : "memory");
        TSW(0, 16 + s); TSW(4, 48 + s); TS8(16 + s);
        const uint32_t al = a16 + (xo >> 4), bl = b16w + (wo >> 4);
        wgmma_fence();
#pragma unroll
        for (int kk = 0; kk < 4; kk++) {
            const uint64_t db = dscB(bl + kk * (2 * CHUNK_BYTES >> 4));
            wgmma_m64n224k16(acc0, dscA(al + kk * 2), db, in_loop || (s | kk) != 0);
            wgmma_m64n224k16(acc1, dscA(al + kk * 2 + (8192 >> 4)), db, in_loop || (s | kk) != 0);
        }
        wgmma_commit();
        asm volatile("bar.arrive %0, 256;" ::"r"(3 - wg) : "memory");
        TSW(0, 32 + s); TSW(4, 64 + s);
    };
    auto advance = [&]() {
        wo_prev = wo;
        xo = xo == 2 * X_BYTES ? 0 : xo + X_BYTES;
        wo = wo == 2 * W_BYTES ? 0 : wo + W_BYTES;
        wnext += 8 * BN;
    };
    batch(0, false);
#pragma unroll 1
    for (int s = 0; s < 9; s++) {
        const uint32_t bs = bars + 8 * s;
        if (warp == 7) {
            const int fb = (int)(W_FLAG >> (4 * s)) & 15, pb = (int)(R_BATCH >> (4 * s)) & 15;
            unsigned* fp = ptr_add(myflags, fb * 4);
            unsigned fv = target;
            const uint32_t l1 = (L1_MASK >> s) & 1, l2 = (L2_MASK >> s) & 1;
            if (W3D && s == 1) wait_until(clk(), W3D);
            if (fb) fv = ld_flag(fp);
            else e_bulk_p(l1, bs + 8 * (B_FULL + 2), W_BYTES, sbase + OFF_W + wo_prev, wnext);
            if (s == 0) {
                issue_x(2, 2);
                wait_until(clk(), W2D);
                e_bulk_p(1, bs + 8 * (B_FULL + 2), W_BYTES, sbase + OFF_W + wo_prev, wnext);
            }
            TSW(7, 112 + s);
            if (pb) {
                mbar_wait(bars + 8 * (B_DQ + pb));
                mbar_wait(bs + 8 * B_EMPTY);
                e_publish(ptr_add(myflags, pb * 4));
            } else {
                if (fb) {
                    finish_poll(fp, fv, target);
                    e_bulk_p(l1, bs + 8 * (B_FULL + 2), W_BYTES, sbase + OFF_W + wo_prev, wnext);
                }
                mbar_wait(bs + 8 * B_EMPTY);
                if (s == 8) {
                    issue_w(12, 3, B_WF);
                    e_bulk(bars + 8 * (B_WF + 3), W_BYTES / 2, sbase + OFF_LUT, wgrp + 15 * 8 * BN);
                }
            }
            wgmma_wait<0>();
            e_bulk_p(l2, bs + 8 * (B_FULL + 3), W_BYTES, sbase + OFF_W + wo, wnext + 8 * BN);
            e_tma(bs + 8 * (B_FULL + 3), &tmx, sbase + OFF_X + xo, (s + 3) * BK, mt * BM);
            TSW(7, 96 + s);
        } else {
            const int r = s + wg;
            if (r == 0) {
                load_raw(4);
                if (warp == 3) {
                    wait_until(clk(), W1D);
                    e_bulk_p(1, bars + 8 * (B_FULL + 1), W_BYTES, sbase + OFF_W + W_BYTES, wgrp + 8 * BN);
                }
            }
            if (wg == 0 && s < 2) coop(s + 3);
            else if (r < 8) { coop(2 * r + 1); if (r < 7) coop(2 * r + 2); }
            const int b = (int)(R_BATCH >> (4 * r)) & 15;
            if (b) { __syncwarp(); e_arrive(bars + 8 * (B_DQ + b)); }
            TSW(0, 80 + s);
            wgmma_wait<0>();
            if (warp == 3) e_arrive(bs + 8 * B_EMPTY);
            if (PFM == 1 && warp == 2 && (s & 3) == 1) pf_x(s + 4);
            if (PFM == 2 && warp == 2 && s == 5) pf_x(9);
            if (PFM == 4 && warp == 2 && s == PFW) pf_x(12);
            if (PFM == 4 && PFE && warp == 2 && (s == PFE || s == PFE + 4)) pf_x(s + 8 - PFE - 4);
        }
        advance();
        batch(s + 1, true);
    }
    {
        if (warp == 7) { if (PFM >= 1 && PFM <= 3) pf_x(13); mbar_wait(bars + 8 * (B_EMPTY + 9)); }
        wgmma_wait<0>();
        if (warp == 3) e_arrive(bars + 8 * (B_EMPTY + 9));
        if (warp == 7) {
            issue_w(13, 0, B_WF + 1);
            e_expect(bars + 8 * B_XV, X_BYTES);
            issue_xv(12, 0, bars + 8 * B_XV); issue_xv(12, 1, bars + 8 * B_XV);
        }
        advance();
        batch(10, false);
        if (warp == 7) mbar_wait(bars + 8 * (B_EMPTY + 10));
        else {
            mbar_wait(bars + 8 * (B_FULL + 11));
#pragma unroll
            for (int t = 1; t <= NFAST; t++) stg128(unit(t, warp), make_uint4(0, 0, 0, 0));
        }
        wgmma_wait<0>();
        if (warp == 3) e_arrive(bars + 8 * (B_EMPTY + 10));
    }

    const int w4 = warp & 3;
    __nv_bfloat16* o = ptr_add(out, (uint32_t)(((mt * BM + wg * 128 + w4 * 16 + (lane >> 2)) * F_ + g * BN + (lane & 3) * 8) * 2));
    auto wofs = [](int st, int kk) -> uint32_t {
        return st < 15 ? OFF_W + (st == 11 ? 2 : st == 12 ? 3 : st - 13) * W_BYTES + kk * 2 * CHUNK_BYTES
                       : kk < 2 ? OFF_LUT + kk * 2 * CHUNK_BYTES : OFF_X + 2 * X_BYTES + (kk - 2) * 16384;
    };
    auto xofs = [](int st, int kk, int r) -> uint32_t {
        return (st == 11 ? 2 * X_BYTES + r * 8192 : ((st - 12) >> 1) * X_BYTES + (st & 1) * 8192) + kk * 32;
    };
    auto launder = [&]() { uint32_t b16 = (sbase & 0x3FFFF) >> 4; asm volatile("mov.u32 %0, %0;" : "+r"(b16)); return b16; };
    auto dA = [&](uint32_t b16, uint32_t ofs) { return dscA(b16 + wg * 1024 + (ofs >> 4) + (uint32_t)descA_hi); };
    auto dB = [&](uint32_t b16, uint32_t ofs) { return dscB(b16 + (ofs >> 4) + (uint32_t)descB_hi); };
    {
        mbar_wait(bars + 8 * (B_FULL + 11));
        asm volatile("bar.sync %0, 256;" ::"r"(2 + wg) : "memory");
        const uint32_t b16 = launder();
        wgmma_fence();
#pragma unroll
        for (int kk = 0; kk < 4; kk++) wgmma_m64n224k16(acc0, dA(b16, xofs(11, kk, 0)), dB(b16, wofs(11, kk)), 1);
        wgmma_commit();
        asm volatile("bar.arrive %0, 256;" ::"r"(3 - wg) : "memory");
        if (warp == 7) {
            issue_w(14, 1, B_WF + 2);
            e_expect(bars + 8 * (B_XV + 1), X_BYTES);
            issue_xv(13, 0, bars + 8 * (B_XV + 1)); issue_xv(13, 1, bars + 8 * (B_XV + 1));
            mbar_wait(bars + 8 * (B_EMPTY + 11));
        }
        wgmma_wait<0>();
        if (warp == 3) e_arrive(bars + 8 * (B_EMPTY + 11));
        if (warp == 7) {
            e_bulk(bars + 8 * (B_WF + 4), 2 * CHUNK_BYTES, sbase + wofs(15, 2), wgrp + (15 * 8 + 4) * BN);
            e_bulk(bars + 8 * (B_XV + 4), 2 * CHUNK_BYTES, sbase + wofs(15, 3), wgrp + (15 * 8 + 6) * BN);
        }
    }
    {
        asm volatile("bar.sync %0, 256;" ::"r"(2 + wg) : "memory");
        TSK(0, 28);
        const uint32_t b16 = launder();
#pragma unroll
        for (int st = 12; st < 16; st++) {
            if (!(st & 1)) mbar_wait(bars + 8 * (B_XV + ((st - 12) >> 1)));
            mbar_wait(bars + 8 * (B_WF + st - 12));
            if (!(st & 1)) wgmma_fence();
#pragma unroll
            for (int kk = 0; kk < 4; kk++) {
                if (st == 15 && kk >= 2) mbar_wait(bars + 8 * (kk == 2 ? B_WF + 4 : B_XV + 4));
                wgmma_m64n224k16(acc0, dA(b16, xofs(st, kk, 0)), dB(b16, wofs(st, kk)), 1);
            }
            if (st & 1) wgmma_commit();
        }
        asm volatile("bar.arrive %0, 256;" ::"r"(3 - wg) : "memory");
    }
    float p0[64], p1[32], p2[16];
#pragma unroll
    for (int i = 0; i < 64; i++) asm volatile("add.f32 %0, %1, 0f00000000;" : "=f"(p0[i]) : "f"(acc1[i]));
#pragma unroll
    for (int i = 0; i < 32; i++) asm volatile("add.f32 %0, %1, 0f00000000;" : "=f"(p1[i]) : "f"(acc1[64 + i]));
#pragma unroll
    for (int i = 0; i < 16; i++) asm volatile("add.f32 %0, %1, 0f00000000;" : "=f"(p2[i]) : "f"(acc1[96 + i]));
    wgmma_wait<1>();
    if (w4 == 3) { e_expect(bars + 8 * (B_XV + 2 + wg), X_BYTES / 2); issue_xv(14, wg, bars + 8 * (B_XV + 2 + wg)); }
    wgmma_wait<0>();
    if (w4 == 3) { e_expect(bars + 8 * (B_X15 + wg), X_BYTES / 2); issue_xv(15, wg, bars + 8 * (B_X15 + wg)); }
    TS9(0);
    uint32_t af[80], pk[(14 - CSP) * 4];
    const uint32_t lm = sbase + wg * 16384 + (w4 * 16 + (lane & 15)) * 128 + (((lane >> 4) ^ (lane & 7)) << 4);
    auto ldfrag = [&](int st) {
#pragma unroll
        for (int kk = 0; kk < 4; kk++) {
            uint32_t* r = af + ((st - 11) * 4 + kk) * 4;
            asm volatile("ldmatrix.sync.aligned.m8n8.x4.shared.b16 {%0,%1,%2,%3}, [%4];" : "=r"(r[0]), "=r"(r[1]), "=r"(r[2]), "=r"(r[3])
                         : "r"((lm ^ (kk << 5)) + xofs(st, 0, 1)) : "memory");
        }
    };
    unsigned tb = clk();
#pragma unroll
    for (int h = 0; h < CSP; h++) {
        if (h >= PSF) wait_until(tb, (h - PSF + 1) * PSTA);
        store_half(acc0, o, h);
        if (h == L11) ldfrag(11);
        if (h == L12) { mbar_wait(bars + 8 * (B_XV + 2 + wg)); ldfrag(12); }
    }
#pragma unroll
    for (int h = CSP; h < 14; h++) pack_half(acc0, h, pk + (h - CSP) * 4);
    asm volatile("bar.sync %0, 256;" ::"r"(2 + wg) : "memory");
    uint32_t b16 = launder();
#pragma unroll
    for (int st = 11; st < 16; st++) {
        wgmma_fence();
#pragma unroll
        for (int kk = 0; kk < 4; kk++) {
            const int i = (st - 11) * 4 + kk;
            wgmma_rs(p0, af + i * 4, dB(b16, wofs(st, kk)));
            if (i == 0) TS9(1);
            if (kk == 0 && st < 14) {
                if (st == 12) mbar_wait(bars + 8 * (B_X15 + wg));
                ldfrag(st + 2);
            }
            if (!(i & 1) && CSP + i / 2 < 14) store_packed(o, CSP + i / 2, pk + (i / 2) * 4);
        }
    }
    wgmma_commit();
    asm volatile("bar.arrive %0, 256;" ::"r"(3 - wg) : "memory");
    TS9(2);
    wgmma_wait<0>();
    TS9(3);
    tb = clk();
#pragma unroll
    for (int h = 0; h < DSP; h++) { wait_until(tb, wg ? h * PSTD : PSB0 + h * PSTB); store_half(p0, o + 64 * F_, h); }
    if (wg == 0) {
#pragma unroll
        for (int h = DSP; h < 8; h++) { wait_until(tb, PSB0 + h * PSTB); store_half(p0, o + 64 * F_, h); }
    }
    asm volatile("bar.sync %0, 256;" ::"r"(2 + wg) : "memory");
    b16 = launder();
    wgmma_fence();
#pragma unroll
    for (int i = 0; i < 20; i++) {
        wgmma_rs(p1, af + i * 4, dB(b16, wofs(11 + (i >> 2), i & 3) + 128 * 16));
        if (!(i & 1) && DSP + i / 2 < 8) store_half(p0, o + 64 * F_, DSP + i / 2, wg);
    }
    wgmma_commit();
    asm volatile("bar.arrive %0, 256;" ::"r"(3 - wg) : "memory");
    wgmma_wait<0>();
    TS9(4);
#pragma unroll
    for (int h = 0; h < 4; h++) store_half(p1, o + 64 * F_ + 128, h);
    asm volatile("bar.sync %0, 256;" ::"r"(2 + wg) : "memory");
    wgmma_fence();
#pragma unroll
    for (int i = 0; i < 20; i++) wgmma_rs(p2, af + i * 4, dB(b16, wofs(11 + (i >> 2), i & 3) + 192 * 16));
    wgmma_commit();
    if (wg == 0) asm volatile("bar.arrive 3, 256;" ::: "memory");
    wgmma_wait<0>();
    TSK(4, 63);
    store_half(p2, o + 64 * F_ + 192, 0);
    store_half(p2, o + 64 * F_ + 192, 1);
}

typedef CUresult (*EncodeTiledFn)(CUtensorMap*, CUtensorMapDataType, cuuint32_t, void*, const cuuint64_t*, const cuuint64_t*, const cuuint32_t*, const cuuint32_t*, CUtensorMapInterleave, CUtensorMapSwizzle, CUtensorMapL2promotion, CUtensorMapFloatOOBfill);

extern "C" void kernel_launch(void* const* d_in, const int* in_sizes, int n_in, void* d_out, int out_size) {
    static EncodeTiledFn enc = nullptr;
    static decltype(&fused_kernel<true>) kern = nullptr;
    static void *p_w = nullptr, *p_flags = nullptr, *p_prof = nullptr;
    if (!enc) {
        void* fn = nullptr; cudaDriverEntryPointQueryResult qr;
        cudaGetDriverEntryPoint("cuTensorMapEncodeTiled", &fn, cudaEnableDefault, &qr);
        enc = (EncodeTiledFn)fn;
        int dev = 0, rsv = 0;
        cudaGetDevice(&dev);
        cudaDeviceGetAttribute(&rsv, cudaDevAttrReservedSharedMemoryPerBlock, dev);
        kern = rsv == 1024 && !NOHARD ? fused_kernel<true> : fused_kernel<false>;
        cudaFuncSetAttribute(kern, cudaFuncAttributeMaxDynamicSharedMemorySize, SMEM_BYTES);
        cudaGetSymbolAddress(&p_w, g_w);
        cudaGetSymbolAddress(&p_flags, g_flags);
    }
    CUtensorMap tmx, tmx64, tmq;
    {
        cuuint64_t gdim[2] = {(cuuint64_t)F_, (cuuint64_t)D_};
        cuuint64_t gstr[1] = {(cuuint64_t)F_ * 4};
        cuuint32_t box[2] = {(cuuint32_t)BN, 16};
        cuuint32_t estr[2] = {1, 1};
        enc(&tmq, CU_TENSOR_MAP_DATA_TYPE_INT32, 2, d_in[1], gdim, gstr, box, estr, CU_TENSOR_MAP_INTERLEAVE_NONE,
            CU_TENSOR_MAP_SWIZZLE_NONE, CU_TENSOR_MAP_L2_PROMOTION_L2_128B, CU_TENSOR_MAP_FLOAT_OOB_FILL_NONE);
    }
    {
        cuuint64_t gdim[2] = {(cuuint64_t)D_, (cuuint64_t)S_};
        cuuint64_t gstr[1] = {(cuuint64_t)D_ * 2};
        cuuint32_t box[2] = {(cuuint32_t)BK, (cuuint32_t)BM};
        cuuint32_t estr[2] = {1, 1};
        enc(&tmx, CU_TENSOR_MAP_DATA_TYPE_BFLOAT16, 2, d_in[0], gdim, gstr, box, estr, CU_TENSOR_MAP_INTERLEAVE_NONE,
            CU_TENSOR_MAP_SWIZZLE_128B, CU_TENSOR_MAP_L2_PROMOTION_L2_128B, CU_TENSOR_MAP_FLOAT_OOB_FILL_NONE);
        box[1] = 64;
        enc(&tmx64, CU_TENSOR_MAP_DATA_TYPE_BFLOAT16, 2, d_in[0], gdim, gstr, box, estr, CU_TENSOR_MAP_INTERLEAVE_NONE,
            CU_TENSOR_MAP_SWIZZLE_128B, CU_TENSOR_MAP_L2_PROMOTION_L2_128B, CU_TENSOR_MAP_FLOAT_OOB_FILL_NONE);
    }
    kern<<<128, 256, SMEM_BYTES>>>((const int*)d_in[1], (const unsigned short*)d_in[2], (__nv_bfloat16*)d_out, (uint4*)p_w, (unsigned*)p_flags, tmq, tmx64, tmx
    );
    (void)p_prof;
}
```

```cpp
#include <cuda_runtime.h>
#include <cuda_bf16.h>
#include <cuda.h>
#include <stdint.h>
#include <stdio.h>

#define PR1 1100
#define PX0 1000
#define PX0B 2500
#define PR2 1900
#define W1D 250
#define W2D 500
#define W3D 600
#define R1E 1
#define X1E 0
#define MAP 1
#define PFM 4
#define PFW 8
#define PFE 0
#define NOW 2
#define PSL 0
#define PSL2 0
#define R3A 3
#define R2A 1
#define R4A 0
#define W4L2 0
#define PF0 0
#define PF1 0
#define STM 0
#define STOP ""
#define VG16 0
#define CSP 10
#define PSTA 110
#define PSF 3
#define L11 3
#define L12 7
#define DSP 4
#define PSB0 150
#define PSTB 110
#define PSTD 100

#define NOHARD 0

constexpr int S_ = 2048, D_ = 1024, F_ = 3584;
constexpr int BM = 256, BN = 224, BK = 64;
constexpr int X_BYTES = BM * BK * 2;
constexpr int W_BYTES = BN * BK * 2;
constexpr int CHUNK_BYTES = BN * 16;
constexpr int SLAB_BYTES = 16 * BN * 4;
constexpr int OFF_X = 0;
constexpr int OFF_W = 3 * X_BYTES;
constexpr int OFF_STG = OFF_W + 3 * W_BYTES;
constexpr int OFF_LUT = OFF_W + 4 * W_BYTES;
constexpr int OFF_BAR = OFF_LUT + 7 * 2048;
constexpr int OFF_PROF = OFF_BAR + 1024;
constexpr int SMEM_BYTES = OFF_PROF + 1024 + 1024;
constexpr int OFF_SLAB0 = OFF_W + 2 * W_BYTES, OFF_SLAB2 = OFF_X + 2 * X_BYTES;
constexpr int B_FULL = 0;
constexpr int B_XV = 12;
constexpr int B_WF = 17;
constexpr int B_EMPTY = 22;
constexpr int B_X0B = 34;
constexpr int B_X15 = 35;
constexpr int B_DQ = 34;
constexpr int B_SLAB = 42;
constexpr int B_LUT = 46;
constexpr int NFAST = 4;
constexpr unsigned long long R_BATCH = 0x60050400ull, W_FLAG = 0x600504000ull;
constexpr unsigned L1_MASK = W4L2 ? 0x2A : 0x2E, L2_MASK = W4L2 ? 0x1EA : 0x1E8;

__device__ __align__(1024) uint4 g_w[(size_t)F_ * D_ / 8];
__device__ __align__(128) unsigned g_flags[16 * 32];

__device__ __forceinline__ uint32_t smem_u32(const void* p) { return (uint32_t)__cvta_generic_to_shared(p); }
__device__ __forceinline__ void mbar_init(uint32_t bar, uint32_t cnt) { asm volatile("mbarrier.init.shared::cta.b64 [%0], %1;" ::"r"(bar), "r"(cnt) : "memory"); }
__device__ __forceinline__ void mbar_wait(uint32_t bar) {
    asm volatile("{\n.reg .pred p;\nWAIT_LOOP:\nmbarrier.try_wait.parity.shared::cta.b64 p, [%0], 0;\n@p bra WAIT_DONE;\nbra WAIT_LOOP;\nWAIT_DONE:\n}" ::"r"(bar) : "memory");
}
__device__ __forceinline__ void e_arrive(uint32_t bar) {
    asm volatile("{\n.reg .pred p;\nelect.sync _|p, 0xffffffff;\n@p mbarrier.arrive.shared::cta.b64 _, [%0];\n}" ::"r"(bar) : "memory");
}
__device__ __forceinline__ void e_expect(uint32_t bar, uint32_t bytes) {
    asm volatile("{\n.reg .pred p;\nelect.sync _|p, 0xffffffff;\n@p mbarrier.arrive.expect_tx.shared::cta.b64 _, [%0], %1;\n}" ::"r"(bar), "r"(bytes) : "memory");
}
__device__ __forceinline__ void e_tma(uint32_t bar, const CUtensorMap* tm, uint32_t d0, int x0, int y0) {
    asm volatile("{\n.reg .pred p;\nelect.sync _|p, 0xffffffff;\n"
                 "@p cp.async.bulk.tensor.2d.shared::cluster.global.mbarrier::complete_tx::bytes [%2], [%1, {%3, %4}], [%0];\n}"
                 ::"r"(bar), "l"(tm), "r"(d0), "r"(x0), "r"(y0) : "memory");
}
__device__ __forceinline__ void e_bulk(uint32_t bar, uint32_t bytes, uint32_t dst, const void* src) {
    asm volatile("{\n.reg .pred p;\nelect.sync _|p, 0xffffffff;\n"
                 "@p mbarrier.arrive.expect_tx.shared::cta.b64 _, [%0], %1;\n"
                 "@p cp.async.bulk.shared::cluster.global.mbarrier::complete_tx::bytes [%2], [%3], %1, [%0];\n}"
                 ::"r"(bar), "r"(bytes), "r"(dst), "l"(src) : "memory");
}
__device__ __forceinline__ void e_bulk_p(uint32_t on, uint32_t bar, uint32_t bytes, uint32_t dst, const void* src) {
    if (on) asm volatile("{\n.reg .pred p;\nelect.sync _|p, 0xffffffff;\n"
                         "@p cp.async.bulk.shared::cluster.global.mbarrier::complete_tx::bytes [%2], [%3], %1, [%0];\n}"
                         ::"r"(bar), "r"(bytes), "r"(dst), "l"(src) : "memory");
}
__device__ __forceinline__ void e_publish(unsigned* flag) {
    asm volatile("{\n.reg .pred p;\nelect.sync _|p, 0xffffffff;\n@p red.release.gpu.global.add.u32 [%0], 1;\n}" ::"l"(flag) : "memory");
}
__device__ __forceinline__ unsigned ld_flag(const unsigned* f) { unsigned v; asm volatile("ld.relaxed.gpu.global.u32 %0, [%1];" : "=r"(v) : "l"(f) : "memory"); return v; }
__device__ __forceinline__ void finish_poll(const unsigned* f, unsigned v, unsigned target) {
    int n = 0;
    while (!__all_sync(0xffffffff, (int)(v - target) >= 0) && ++n < 4000000) v = ld_flag(f);
    asm volatile("fence.acquire.gpu;" ::: "memory");
    asm volatile("fence.proxy.async.global;" ::: "memory");
}
template <typename T> __device__ __forceinline__ T* ptr_add(T* base, uint32_t off) {
    uint64_t r;
    asm("{\n.reg .u32 l, h;\nmov.b64 {l, h}, %1;\nadd.cc.u32 l, l, %2;\naddc.u32 h, h, 0;\nmov.b64 %0, {l, h};\n}" : "=l"(r) : "l"(base), "r"(off));
    return (T*)r;
}
__device__ __forceinline__ void wgmma_fence() { asm volatile("wgmma.fence.sync.aligned;" ::: "memory"); }
__device__ __forceinline__ void wgmma_commit() { asm volatile("wgmma.commit_group.sync.aligned;" ::: "memory"); }
template <int N> __device__ __forceinline__ void wgmma_wait() { asm volatile("wgmma.wait_group.sync.aligned %0;" ::"n"(N) : "memory"); }
__device__ __forceinline__ void wgmma_m64n224k16(float (&d)[112], uint64_t da, uint64_t db, int scale_d) {
    asm volatile(
        "{\n.reg .pred p;\nsetp.ne.b32 p, %114, 0;\n"
        "wgmma.mma_async.sync.aligned.m64n224k16.f32.bf16.bf16 "
        "{%0, %1, %2, %3, %4, %5, %6, %7, %8, %9, %10, %11, %12, %13, %14, %15, "
        "%16, %17, %18, %19, %20, %21, %22, %23, %24, %25, %26, %27, %28, %29, %30, %31, "
        "%32, %33, %34, %35, %36, %37, %38, %39, %40, %41, %42, %43, %44, %45, %46, %47, "
        "%48, %49, %50, %51, %52, %53, %54, %55, %56, %57, %58, %59, %60, %61, %62, %63, "
        "%64, %65, %66, %67, %68, %69, %70, %71, %72, %73, %74, %75, %76, %77, %78, %79, "
        "%80, %81, %82, %83, %84, %85, %86, %87, %88, %89, %90, %91, %92, %93, %94, %95, "
        "%96, %97, %98, %99, %100, %101, %102, %103, %104, %105, %106, %107, %108, %109, %110, %111}, "
        "%112, %113, p, 1, 1, 0, 0;\n}\n"
        : "+f"(d[0]), "+f"(d[1]), "+f"(d[2]), "+f"(d[3]), "+f"(d[4]), "+f"(d[5]), "+f"(d[6]), "+f"(d[7]),
          "+f"(d[8]), "+f"(d[9]), "+f"(d[10]), "+f"(d[11]), "+f"(d[12]), "+f"(d[13]), "+f"(d[14]), "+f"(d[15]),
          "+f"(d[16]), "+f"(d[17]), "+f"(d[18]), "+f"(d[19]), "+f"(d[20]), "+f"(d[21]), "+f"(d[22]), "+f"(d[23]),
          "+f"(d[24]), "+f"(d[25]), "+f"(d[26]), "+f"(d[27]), "+f"(d[28]), "+f"(d[29]), "+f"(d[30]), "+f"(d[31]),
          "+f"(d[32]), "+f"(d[33]), "+f"(d[34]), "+f"(d[35]), "+f"(d[36]), "+f"(d[37]), "+f"(d[38]), "+f"(d[39]),
          "+f"(d[40]), "+f"(d[41]), "+f"(d[42]), "+f"(d[43]), "+f"(d[44]), "+f"(d[45]), "+f"(d[46]), "+f"(d[47]),
          "+f"(d[48]), "+f"(d[49]), "+f"(d[50]), "+f"(d[51]), "+f"(d[52]), "+f"(d[53]), "+f"(d[54]), "+f"(d[55]),
          "+f"(d[56]), "+f"(d[57]), "+f"(d[58]), "+f"(d[59]), "+f"(d[60]), "+f"(d[61]), "+f"(d[62]), "+f"(d[63]),
          "+f"(d[64]), "+f"(d[65]), "+f"(d[66]), "+f"(d[67]), "+f"(d[68]), "+f"(d[69]), "+f"(d[70]), "+f"(d[71]),
          "+f"(d[72]), "+f"(d[73]), "+f"(d[74]), "+f"(d[75]), "+f"(d[76]), "+f"(d[77]), "+f"(d[78]), "+f"(d[79]),
          "+f"(d[80]), "+f"(d[81]), "+f"(d[82]), "+f"(d[83]), "+f"(d[84]), "+f"(d[85]), "+f"(d[86]), "+f"(d[87]),
          "+f"(d[88]), "+f"(d[89]), "+f"(d[90]), "+f"(d[91]), "+f"(d[92]), "+f"(d[93]), "+f"(d[94]), "+f"(d[95]),
          "+f"(d[96]), "+f"(d[97]), "+f"(d[98]), "+f"(d[99]), "+f"(d[100]), "+f"(d[101]), "+f"(d[102]), "+f"(d[103]),
          "+f"(d[104]), "+f"(d[105]), "+f"(d[106]), "+f"(d[107]), "+f"(d[108]), "+f"(d[109]), "+f"(d[110]), "+f"(d[111])
        : "l"(da), "l"(db), "r"(scale_d));
}

__device__ __forceinline__ void wgmma_rs(float (&d)[16], const uint32_t* a, uint64_t db) {
    asm volatile("wgmma.mma_async.sync.aligned.m64n32k16.f32.bf16.bf16 {%0, %1, %2, %3, %4, %5, %6, %7, %8, %9, %10, %11, %12, %13, %14, %15}, {%16, %17, %18, %19}, %20, 1, 1, 1, 0;"
        : "+f"(d[0]), "+f"(d[1]), "+f"(d[2]), "+f"(d[3]), "+f"(d[4]), "+f"(d[5]), "+f"(d[6]), "+f"(d[7]), "+f"(d[8]), "+f"(d[9]), "+f"(d[10]), "+f"(d[11]), "+f"(d[12]), "+f"(d[13]), "+f"(d[14]), "+f"(d[15])
        : "r"(a[0]), "r"(a[1]), "r"(a[2]), "r"(a[3]), "l"(db));
}
__device__ __forceinline__ void wgmma_rs(float (&d)[32], const uint32_t* a, uint64_t db) {
    asm volatile("wgmma.mma_async.sync.aligned.m64n64k16.f32.bf16.bf16 {%0, %1, %2, %3, %4, %5, %6, %7, %8, %9, %10, %11, %12, %13, %14, %15, %16, %17, %18, %19, %20, %21, %22, %23, %24, %25, %26, %27, %28, %29, %30, %31}, {%32, %33, %34, %35}, %36, 1, 1, 1, 0;"
        : "+f"(d[0]), "+f"(d[1]), "+f"(d[2]), "+f"(d[3]), "+f"(d[4]), "+f"(d[5]), "+f"(d[6]), "+f"(d[7]), "+f"(d[8]), "+f"(d[9]), "+f"(d[10]), "+f"(d[11]), "+f"(d[12]), "+f"(d[13]), "+f"(d[14]), "+f"(d[15]), "+f"(d[16]), "+f"(d[17]), "+f"(d[18]), "+f"(d[19]), "+f"(d[20]), "+f"(d[21]), "+f"(d[22]), "+f"(d[23]), "+f"(d[24]), "+f"(d[25]), "+f"(d[26]), "+f"(d[27]), "+f"(d[28]), "+f"(d[29]), "+f"(d[30]), "+f"(d[31])
        : "r"(a[0]), "r"(a[1]), "r"(a[2]), "r"(a[3]), "l"(db));
}
__device__ __forceinline__ void wgmma_rs(float (&d)[64], const uint32_t* a, uint64_t db) {
    asm volatile("wgmma.mma_async.sync.aligned.m64n128k16.f32.bf16.bf16 {%0, %1, %2, %3, %4, %5, %6, %7, %8, %9, %10, %11, %12, %13, %14, %15, %16, %17, %18, %19, %20, %21, %22, %23, %24, %25, %26, %27, %28, %29, %30, %31, %32, %33, %34, %35, %36, %37, %38, %39, %40, %41, %42, %43, %44, %45, %46, %47, %48, %49, %50, %51, %52, %53, %54, %55, %56, %57, %58, %59, %60, %61, %62, %63}, {%64, %65, %66, %67}, %68, 1, 1, 1, 0;"
        : "+f"(d[0]), "+f"(d[1]), "+f"(d[2]), "+f"(d[3]), "+f"(d[4]), "+f"(d[5]), "+f"(d[6]), "+f"(d[7]), "+f"(d[8]), "+f"(d[9]), "+f"(d[10]), "+f"(d[11]), "+f"(d[12]), "+f"(d[13]), "+f"(d[14]), "+f"(d[15]), "+f"(d[16]), "+f"(d[17]), "+f"(d[18]), "+f"(d[19]), "+f"(d[20]), "+f"(d[21]), "+f"(d[22]), "+f"(d[23]), "+f"(d[24]), "+f"(d[25]), "+f"(d[26]), "+f"(d[27]), "+f"(d[28]), "+f"(d[29]), "+f"(d[30]), "+f"(d[31]), "+f"(d[32]), "+f"(d[33]), "+f"(d[34]), "+f"(d[35]), "+f"(d[36]), "+f"(d[37]), "+f"(d[38]), "+f"(d[39]), "+f"(d[40]), "+f"(d[41]), "+f"(d[42]), "+f"(d[43]), "+f"(d[44]), "+f"(d[45]), "+f"(d[46]), "+f"(d[47]), "+f"(d[48]), "+f"(d[49]), "+f"(d[50]), "+f"(d[51]), "+f"(d[52]), "+f"(d[53]), "+f"(d[54]), "+f"(d[55]), "+f"(d[56]), "+f"(d[57]), "+f"(d[58]), "+f"(d[59]), "+f"(d[60]), "+f"(d[61]), "+f"(d[62]), "+f"(d[63])
        : "r"(a[0]), "r"(a[1]), "r"(a[2]), "r"(a[3]), "l"(db));
}

__device__ __forceinline__ uint32_t pack_bf16(float lo, float hi) {
    uint32_t r; asm("cvt.rn.bf16x2.f32 %0, %1, %2;" : "=r"(r) : "f"(hi), "f"(lo)); return r;
}
__device__ __forceinline__ uint32_t lds32(uint32_t a) { uint32_t v; asm volatile("ld.shared.b32 %0, [%1];" : "=r"(v) : "r"(a)); return v; }
__device__ __forceinline__ void sts32(uint32_t a, uint32_t v) { asm volatile("st.shared.b32 [%0], %1;" ::"r"(a), "r"(v) : "memory"); }
__device__ __forceinline__ void sts128(uint32_t a, uint4 v) { asm volatile("st.shared.v4.b32 [%0], {%1,%2,%3,%4};" ::"r"(a), "r"(v.x), "r"(v.y), "r"(v.z), "r"(v.w) : "memory"); }
__device__ __forceinline__ void stg128(void* p, uint4 v) { asm volatile("st.global.v4.b32 [%0], {%1,%2,%3,%4};" ::"l"(p), "r"(v.x), "r"(v.y), "r"(v.z), "r"(v.w) : "memory"); }
__device__ __forceinline__ void cp16(uint32_t dst, const void* src) { asm volatile("cp.async.cg.shared.global [%0], [%1], 16;" ::"r"(dst), "l"(src) : "memory"); }
__device__ __forceinline__ void cp_commit() { asm volatile("cp.async.commit_group;" ::: "memory"); }
template <int N> __device__ __forceinline__ void cp_wait() { asm volatile("cp.async.wait_group %0;" ::"n"(N) : "memory"); }
__device__ __forceinline__ uint4 dequant8(uint32_t raw, uint32_t lut_a) {
    uint32_t v[8];
#pragma unroll
    for (int i = 0; i < 8; i++) v[i] = lds32(raw + i * 128);
#pragma unroll
    for (int i = 0; i < 8; i++) v[i] = lds32(lut_a + v[i] * 128);
    uint4 o;
    o.x = __byte_perm(v[0], v[1], 0x5410); o.y = __byte_perm(v[2], v[3], 0x5410);
    o.z = __byte_perm(v[4], v[5], 0x5410); o.w = __byte_perm(v[6], v[7], 0x5410);
    return o;
}
__device__ __forceinline__ uint32_t prmt(uint32_t a, uint32_t b, uint32_t c) { uint32_t r; asm("prmt.b32 %0, %1, %2, %3;" : "=r"(r) : "r"(a), "r"(b), "r"(c)); return r; }
__device__ __forceinline__ uint4 lookup8_reg(const uint32_t* c, const uint32_t (&T)[8]) {
    uint32_t o[4];
#pragma unroll
    for (int h = 0; h < 2; h++) {
        const uint32_t sel = c[4 * h] + c[4 * h + 1] * 16 + c[4 * h + 2] * 256 + c[4 * h + 3] * 4096;
        const uint32_t s7 = sel & 0x7777u;
        uint32_t m;
        asm("lop3.b32 %0, %1, %2, 0x3210, 0xEA;" : "=r"(m) : "r"(sel >> 1), "r"(0x4444u));
        const uint32_t lo = prmt(prmt(T[0], T[1], s7), prmt(T[2], T[3], s7), m);
        const uint32_t hi = prmt(prmt(T[4], T[5], s7), prmt(T[6], T[7], s7), m);
        o[2 * h] = prmt(lo, hi, 0x5140u); o[2 * h + 1] = prmt(lo, hi, 0x7362u);
    }
    return make_uint4(o[0], o[1], o[2], o[3]);
}
template <int N>
__device__ __forceinline__ void pack_half(const float (&acc)[N], int H, uint32_t* r) {
    const int b = (H >> 1) * 16 + (H & 1) * 2;
#pragma unroll
    for (int i = 0; i < 4; i++) asm volatile("cvt.rn.bf16x2.f32 %0, %1, %2;" : "=r"(r[i]) : "f"(acc[b + 4 * i + 1]), "f"(acc[b + 4 * i]));
}
__device__ __forceinline__ void store_packed(__nv_bfloat16* o, int H, const uint32_t* r, int on = 1) {
    asm volatile("{\n.reg .pred p;\nsetp.ne.b32 p, %5, 0;\n@p st.global" STOP ".v4.b32 [%0], {%1,%2,%3,%4};\n}"
                 ::"l"(o + (H & 1) * 8 * F_ + (H >> 1) * 32), "r"(r[0]), "r"(r[1]), "r"(r[2]), "r"(r[3]), "r"(on) : "memory");
}
template <int N>
__device__ __forceinline__ void store_half(const float (&acc)[N], __nv_bfloat16* o, int H, int on = 1) {
    const int b = (H >> 1) * 16 + (H & 1) * 2;
    const uint32_t r[4] = {pack_bf16(acc[b], acc[b + 1]), pack_bf16(acc[b + 4], acc[b + 5]), pack_bf16(acc[b + 8], acc[b + 9]), pack_bf16(acc[b + 12], acc[b + 13])};
    store_packed(o, H, r, on);
}
__device__ __forceinline__ unsigned clk() { unsigned c; asm volatile("mov.u32 %0, %%clock;" : "=r"(c)); return c; }
__device__ __forceinline__ void wait_until(unsigned t0, unsigned dt) { while (clk() - t0 < dt) {} }

#define TSK(w, i)
#define TS8(i)
#define TSW(w, i)
#define TS9(i)

template <bool HARD>
__global__ void __launch_bounds__(256, 1)
fused_kernel(const int* __restrict__ qw, const unsigned short* __restrict__ lut, __nv_bfloat16* __restrict__ out,
             uint4* __restrict__ wscr, unsigned* __restrict__ flags,
             const __grid_constant__ CUtensorMap tmq, const __grid_constant__ CUtensorMap tmx64, const __grid_constant__ CUtensorMap tmx
) {
    extern __shared__ uint8_t smem_raw[];
    const uint32_t sbase = HARD ? 1024u : (smem_u32(smem_raw) + 1023) & ~1023u;
    const uint32_t bars = sbase + OFF_BAR;
    const int tid = threadIdx.x, lane = tid & 31;
    const int mt = (blockIdx.x >> 6) * 4 + (blockIdx.x & 3), g = ((blockIdx.x >> 3) & 7) * 2 + ((blockIdx.x >> 2) & 1);
    const unsigned clk0 = clk();
    const int warp = __shfl_sync(0xffffffff, tid >> 5, 0);
    if (tid >= 224) {
        asm volatile("{\n.reg .pred p;\nelect.sync _|p, 0xffffffff;\n"
                     "@p mbarrier.init.shared::cta.b64 [%0], 1;\n"
                     "@p fence.mbarrier_init.release.cluster;\n"
                     "@p mbarrier.arrive.expect_tx.shared::cta.b64 _, [%0], %1;\n"
                     "@p cp.async.bulk.tensor.2d.shared::cluster.global.mbarrier::complete_tx::bytes [%3], [%2, {%4, 0}], [%0];\n}"
                     ::"r"(bars + 8 * B_SLAB), "n"(SLAB_BYTES), "l"(&tmq), "r"(sbase + OFF_SLAB0), "r"(g * BN) : "memory");
    } else {
        const unsigned short* lp = ptr_add(lut, ((lane >> 2) * F_ + g * BN + (tid & ~31) + (lane & 3) * 8) * 2);
        asm volatile("cp.async.cg.shared.global [%0], [%1], 16;\ncp.async.cg.shared.global [%0+512], [%1+57344], 16;\ncp.async.commit_group;"
                     ::"r"(sbase + OFF_STG + (tid >> 5) * 4096 + lane * 16), "l"(lp) : "memory");
    }
    const int sl = warp - 3;
    auto load_slab = [&]() {
        e_tma(bars + 8 * (B_SLAB + sl), &tmq, sbase + (sl < 2 ? OFF_SLAB0 : OFF_SLAB2 - 2 * SLAB_BYTES) + sl * SLAB_BYTES, g * BN, sl * 16);
    };
    if (warp >= 4 && warp < 7) {
        asm volatile("{\n.reg .pred p;\nelect.sync _|p, 0xffffffff;\n"
                     "@p mbarrier.init.shared::cta.b64 [%0], 1;\n"
                     "@p fence.mbarrier_init.release.cluster;\n"
                     "@p mbarrier.arrive.expect_tx.shared::cta.b64 _, [%0], %1;\n}"
                     ::"r"(bars + 8 * (B_SLAB + sl)), "n"(SLAB_BYTES) : "memory");
        if (sl < NOW) load_slab();
    } else if (warp < 2) {
        asm volatile("{\n.reg .pred p;\nelect.sync _|p, 0xffffffff;\n"
                     "@p mbarrier.init.shared::cta.b64 [%0], %1;\n"
                     "@p fence.mbarrier_init.release.cluster;\n}" ::"r"(bars + 8 * (warp ? B_LUT : B_FULL)), "r"(8 - warp) : "memory");
    }
    asm volatile("bar.sync 1, 256;" ::: "memory");
    const int wg = warp >> 2;

    const int fl = 8 * ((lane & 7) >> 1) + 2 * (lane >> 3) + (lane & 1);
    const uint32_t lut_a = sbase + OFF_LUT + warp * 2048 + lane * 4;
    const uint32_t stg = sbase + OFF_STG + warp * 4096;
    unsigned* myflags = flags + g * 32;
    const uint4* wgrp = wscr + (size_t)g * 128 * BN;
    unsigned target = 0;

    auto issue_x = [&](int s, int slot) {
        e_tma(bars + 8 * (B_FULL + s), &tmx, sbase + OFF_X + slot * X_BYTES, s * BK, mt * BM);
    };
    auto pf_x = [&](int s) {
        asm volatile("{\n.reg .pred p;\nelect.sync _|p, 0xffffffff;\n@p cp.async.bulk.prefetch.tensor.2d.L2.global [%0, {%1, %2}];\n}"
                     ::"l"(&tmx64), "r"((s + (g >> 2)) * BK), "r"(mt * BM + (g & 3) * 64) : "memory");
    };
    auto issue_xv = [&](int v, int w, uint32_t bar) {
        const uint32_t dst = sbase + OFF_X + (v & 1) * X_BYTES + w * 16384;
        const int k0 = (12 + 2 * (v & 1)) * BK, r0 = mt * BM + w * 128 + ((v >> 1) & 1) * 64;
        e_tma(bar, &tmx64, dst, k0, r0);
        e_tma(bar, &tmx64, dst + 8192, k0 + BK, r0);
    };
    auto issue_w = [&](int s, int slot, int bar) {
        e_bulk(bars + 8 * bar, W_BYTES, sbase + OFF_W + slot * W_BYTES, wgrp + s * 8 * BN);
    };
    auto load_blk = [&](int t, int c) {
        const int* src = ptr_add(qw, (uint32_t)(((t * BK + mt * 8 + (lane >> 3)) * F_ + g * BN + c * 32 + (lane & 7) * 4) * 4));
        asm volatile("cp.async.cg.shared.global [%0], [%1], 16;\ncp.async.cg.shared.global [%0+512], [%1+57344], 16;"
                     ::"r"(sbase + OFF_STG + c * 4096 + (t & 3) * 1024 + lane * 16), "l"(src) : "memory");
    };
    auto load_raw = [&](int t) { if (t < 16) load_blk(t, warp); cp_commit(); };
    auto unit = [&](int t, int c) { return ptr_add(wscr, (uint32_t)(((g * 128 + t * 8 + mt) * BN + c * 32 + lane) * 16)); };
    auto foreign2 = [&]() {
        const int c = warp - 4;
        stg128(unit(2, c), dequant8(sbase + OFF_STG + c * 4096 + 2 * 1024 + fl * 4, sbase + OFF_LUT + c * 2048 + lane * 4));
    };
    auto coop = [&](int t) {
        cp_wait<1>();
        __syncwarp();
        load_raw(t + 2);
        stg128(unit(t, warp), dequant8(stg + (t & 3) * 1024 + fl * 4, lut_a));
    };

    if (warp == 7) {
        if (lane == 0) {
            asm volatile("prefetch.tensormap [%0];" ::"l"(&tmx) : "memory");
            asm volatile("prefetch.tensormap [%0];" ::"l"(&tmx64) : "memory");
        }
        __syncwarp();
        auto x0 = [&](int w, uint32_t bar) {
            e_expect(bar, X_BYTES / 2);
            e_tma(bar, &tmx64, sbase + OFF_X + w * 16384, 0, mt * BM + w * 128);
            e_tma(bar, &tmx64, sbase + OFF_X + w * 16384 + 8192, 0, mt * BM + w * 128 + 64);
        };
        wait_until(clk0, PX0);
        x0(0, bars + 8 * B_FULL);
        auto pf = [&](int k, int row) {
            asm volatile("{\n.reg .pred p;\nelect.sync _|p, 0xffffffff;\n@p cp.async.bulk.prefetch.tensor.2d.L2.global [%0, {%1, %2}];\n}" ::"l"(&tmx64), "r"(k), "r"(row) : "memory");
        };
        if (PF0 && g < 2) { wait_until(clk0, PF0); pf(0, mt * BM + 128 + g * 64); }
        target = ld_flag(myflags + 6);
        wait_until(clk0, PR2);
        load_blk(2, 3);
        cp_commit();
        if (PF1 && (g >> 2) == 1) { wait_until(clk0, PF1); pf(BK, mt * BM + (g & 3) * 64); }
        mbar_wait(bars + 8 * B_LUT);
        wait_until(clk0, PX0B);
        x0(1, bars + 8 * B_X0B);
        target = (target | 7) + 1;
        if (X1E) wait_until(clk0, X1E); else mbar_wait(bars + 8 * B_FULL);
        issue_x(1, 1);
        cp_wait<0>();
        __syncwarp();
        foreign2();
        TSW(7, 3);
    } else {
        if (wg == 1 && sl >= NOW) { if (PSL) wait_until(clk0, PSL + (sl - 2) * PSL2); load_slab(); }
        if (lane == 0) {
#pragma unroll
            for (int i = 0; i < 6; i++) {
                const int b = 1 + warp * 6 + i;
                if (b < B_SLAB) mbar_init(bars + 8 * b, b < B_DQ + 4 ? 1 : 7);
                if (b < B_XV) asm volatile("mbarrier.arrive.expect_tx.shared::cta.b64 _, [%0], %1;" ::"r"(bars + 8 * b), "r"(X_BYTES + W_BYTES) : "memory");
            }
            asm volatile("fence.mbarrier_init.release.cluster;" ::: "memory");
        }
        __syncwarp();
        wait_until(clk0, PR1);
        load_raw(1);
        uint32_t lv[16], v[32], T[8];
        cp_wait<1>();
        __syncwarp();
#pragma unroll
        for (int i = 0; i < 16; i++) asm volatile("ld.shared.u16 %0, [%1];" : "=r"(lv[i]) : "r"(stg + i * 64 + fl * 2));
#pragma unroll
        for (int i = 0; i < 16; i++) lv[i] = lv[i] ? lv[i] : 0x8000u;
#pragma unroll
        for (int i = 0; i < 4; i++) {
            const uint32_t p01 = prmt(lv[4 * i], lv[4 * i + 1], 0x5140u), p23 = prmt(lv[4 * i + 2], lv[4 * i + 3], 0x5140u);
            T[i] = prmt(p01, p23, 0x5410u); T[4 + i] = prmt(p01, p23, 0x7632u);
        }
        TSW(0, 7);
#pragma unroll
        for (int i = 0; i < 16; i++) sts32(lut_a + i * 128, lv[i]);
        __syncwarp();
        e_arrive(bars + 8 * B_LUT);
        auto own_task = [&](int t) {
            __syncwarp();
            uint32_t c[8];
#pragma unroll
            for (int i = 0; i < 8; i++) c[i] = lds32(stg + t * 1024 + fl * 4 + i * 128);
            stg128(unit(t, warp), lookup8_reg(c, T));
        };
        auto piece_ld = [&](int j) {
            mbar_wait(bars + 8 * (B_SLAB + j));
#pragma unroll
            for (int i = 0; i < 16; i++) v[(j & 1) * 16 + i] = lds32(sbase + (j < 2 ? OFF_SLAB0 : OFF_SLAB2) + (j & 1) * SLAB_BYTES + i * (BN * 4) + (warp * 32 + fl) * 4);
        };
        auto piece_st = [&](int j) {
            const uint32_t dst = sbase + OFF_W + j * 2 * CHUNK_BYTES + (warp * 32 + lane) * 16;
            sts128(dst, lookup8_reg(v + (j & 1) * 16, T));
            sts128(dst + CHUNK_BYTES, lookup8_reg(v + (j & 1) * 16 + 8, T));
            TSW(0, 8 + j);
        };
        if (R2A == 0 && wg == 1) { load_blk(2, warp); load_blk(2, warp - 4); cp_commit(); }
        piece_ld(0);
        if (R2A == 1 && wg == 1) { load_blk(2, warp); load_blk(2, warp - 4); cp_commit(); }
        piece_st(0);
        if (R2A == 2 && wg == 1) { load_blk(2, warp); load_blk(2, warp - 4); cp_commit(); }
        piece_ld(1);
        piece_ld(2);
        if (R3A == 2 && wg == 0) load_raw(3);
        piece_st(1);
        piece_ld(3);
        if (R3A == 3 && wg == 0) load_raw(3);
        if (R1E == 2) { if (wg == 0) cp_wait<1>(); else cp_wait<1>(); own_task(1); }
        piece_st(2);
        if (R1E == 1) { cp_wait<1>(); own_task(1); }
        piece_st(3);
        asm volatile("fence.proxy.async.shared::cta;" ::: "memory");
        __syncwarp();
        e_arrive(bars + 8 * B_FULL);
        if (!R1E) { if (R3A == 4 && wg == 0) cp_wait<0>(); else cp_wait<1>(); own_task(1); }
        if (R3A == 4 && wg == 0) load_raw(3);
        TSW(0, 14);
        if (wg == 1) {
            load_raw(3);
            cp_wait<1>();
            own_task(2);
            if (R4A == 0) load_raw(4);
            mbar_wait(bars + 8 * B_LUT);
            foreign2();
            if (R4A == 1) load_raw(4);
        }
        TSW(4, 12);
    }

    float acc0[112], acc1[112];
    const uint64_t descA_hi = ((uint64_t)1 << 62) | ((uint64_t)(1024 >> 4) << 32) | ((uint64_t)1 << 16);
    const uint64_t descB_hi = ((uint64_t)(128 >> 4) << 32) | ((uint64_t)(CHUNK_BYTES >> 4) << 16);
    const uint32_t a16 = ((sbase & 0x3FFFF) >> 4) + wg * 1024 + (uint32_t)descA_hi, b16w = (((sbase + OFF_W) & 0x3FFFF) >> 4) + (uint32_t)descB_hi;
    auto dscA = [&](uint32_t lo) { return (descA_hi & 0xFFFFFFFF00000000ull) | lo; };
    auto dscB = [&](uint32_t lo) { return (descB_hi & 0xFFFFFFFF00000000ull) | lo; };
    uint32_t xo = 0, wo = 0, wo_prev = 2 * W_BYTES;
    const uint4* wnext = wgrp + 2 * 8 * BN;
    auto validate = [&](int t) {
        const uint32_t a = sbase + OFF_W + wo;
        for (int n = 0; n < 2000000; n++) {
            uint32_t m = 0xffffffffu;
#pragma unroll
            for (int i = 0; i < 7; i++) {
                if (VG16) { m = min(m, lds32(a + (warp * 64 + lane) * 16 + (lane >> 3) * 4 + i * 4096)); m = min(m, lds32(a + (warp * 64 + 32 + lane) * 16 + (lane >> 3) * 4 + i * 4096)); }
                else m = min(m, lds32(a + tid * 32 + (lane >> 2) * 4 + i * 4096));
            }
            if (__all_sync(0xffffffff, m != 0)) break;
            const uint4* src = ptr_add(wgrp, (uint32_t)((t * 8 * BN + warp * 64 + lane) * 16));
#pragma unroll 1
            for (int i = 0; i < 14; i++) cp16(a + (warp * 64 + lane + (i >> 1) * 256 + (i & 1) * 32) * 16, src + (i >> 1) * 256 + (i & 1) * 32);
            cp_commit();
            cp_wait<0>();
            asm volatile("fence.proxy.async.shared::cta;" ::: "memory");
            __syncwarp();
        }
    };
    auto batch = [&](int s, bool in_loop) {
        mbar_wait(bars + 8 * (B_FULL + s));
        if (!in_loop && s == 0 && wg == 1) mbar_wait(bars + 8 * B_X0B);
        if (in_loop && wg == 0 && s <= NFAST) validate(s);
        if (s + wg > 0) asm volatile("bar.sync %0, 256;" ::"r"(2 + wg) : "memory");
        TSW(0, 16 + s); TSW(4, 48 + s); TS8(16 + s);
        const uint32_t al = a16 + (xo >> 4), bl = b16w + (wo >> 4);
        wgmma_fence();
#pragma unroll
        for (int kk = 0; kk < 4; kk++) {
            const uint64_t db = dscB(bl + kk * (2 * CHUNK_BYTES >> 4));
            wgmma_m64n224k16(acc0, dscA(al + kk * 2), db, in_loop || (s | kk) != 0);
            wgmma_m64n224k16(acc1, dscA(al + kk * 2 + (8192 >> 4)), db, in_loop || (s | kk) != 0);
        }
        wgmma_commit();
        asm volatile("bar.arrive %0, 256;" ::"r"(3 - wg) : "memory");
        TSW(0, 32 + s); TSW(4, 64 + s);
    };
    auto advance = [&]() {
        wo_prev = wo;
        xo = xo == 2 * X_BYTES ? 0 : xo + X_BYTES;
        wo = wo == 2 * W_BYTES ? 0 : wo + W_BYTES;
        wnext += 8 * BN;
    };
    batch(0, false);
#pragma unroll 1
    for (int s = 0; s < 9; s++) {
        const uint32_t bs = bars + 8 * s;
        if (warp == 7) {
            const int fb = (int)(W_FLAG >> (4 * s)) & 15, pb = (int)(R_BATCH >> (4 * s)) & 15;
            unsigned* fp = ptr_add(myflags, fb * 4);
            unsigned fv = target;
            const uint32_t l1 = (L1_MASK >> s) & 1, l2 = (L2_MASK >> s) & 1;
            if (W3D && s == 1) wait_until(clk(), W3D);
            if (fb) fv = ld_flag(fp);
            else e_bulk_p(l1, bs + 8 * (B_FULL + 2), W_BYTES, sbase + OFF_W + wo_prev, wnext);
            if (s == 0) {
                issue_x(2, 2);
                wait_until(clk(), W2D);
                e_bulk_p(1, bs + 8 * (B_FULL + 2), W_BYTES, sbase + OFF_W + wo_prev, wnext);
            }
            TSW(7, 112 + s);
            if (pb) {
                mbar_wait(bars + 8 * (B_DQ + pb));
                mbar_wait(bs + 8 * B_EMPTY);
                e_publish(ptr_add(myflags, pb * 4));
            } else {
                if (fb) {
                    finish_poll(fp, fv, target);
                    e_bulk_p(l1, bs + 8 * (B_FULL + 2), W_BYTES, sbase + OFF_W + wo_prev, wnext);
                }
                mbar_wait(bs + 8 * B_EMPTY);
                if (s == 8) {
                    issue_w(12, 3, B_WF);
                    e_bulk(bars + 8 * (B_WF + 3), W_BYTES / 2, sbase + OFF_LUT, wgrp + 15 * 8 * BN);
                }
            }
            wgmma_wait<0>();
            e_bulk_p(l2, bs + 8 * (B_FULL + 3), W_BYTES, sbase + OFF_W + wo, wnext + 8 * BN);
            e_tma(bs + 8 * (B_FULL + 3), &tmx, sbase + OFF_X + xo, (s + 3) * BK, mt * BM);
            TSW(7, 96 + s);
        } else {
            const int r = s + wg;
            if (r == 0) {
                load_raw(4);
                if (warp == 3) {
                    wait_until(clk(), W1D);
                    e_bulk_p(1, bars + 8 * (B_FULL + 1), W_BYTES, sbase + OFF_W + W_BYTES, wgrp + 8 * BN);
                }
            }
            if (wg == 0 && s < 2) coop(s + 3);
            else if (r < 8) { coop(2 * r + 1); if (r < 7) coop(2 * r + 2); }
            const int b = (int)(R_BATCH >> (4 * r)) & 15;
            if (b) { __syncwarp(); e_arrive(bars + 8 * (B_DQ + b)); }
            TSW(0, 80 + s);
            wgmma_wait<0>();
            if (warp == 3) e_arrive(bs + 8 * B_EMPTY);
            if (PFM == 1 && warp == 2 && (s & 3) == 1) pf_x(s + 4);
            if (PFM == 2 && warp == 2 && s == 5) pf_x(9);
            if (PFM == 4 && warp == 2 && s == PFW) pf_x(12);
            if (PFM == 4 && PFE && warp == 2 && (s == PFE || s == PFE + 4)) pf_x(s + 8 - PFE - 4);
        }
        advance();
        batch(s + 1, true);
    }
    {
        if (warp == 7) { if (PFM >= 1 && PFM <= 3) pf_x(13); mbar_wait(bars + 8 * (B_EMPTY + 9)); }
        wgmma_wait<0>();
        if (warp == 3) e_arrive(bars + 8 * (B_EMPTY + 9));
        if (warp == 7) {
            issue_w(13, 0, B_WF + 1);
            e_expect(bars + 8 * B_XV, X_BYTES);
            issue_xv(12, 0, bars + 8 * B_XV); issue_xv(12, 1, bars + 8 * B_XV);
        }
        advance();
        batch(10, false);
        if (warp == 7) mbar_wait(bars + 8 * (B_EMPTY + 10));
        else {
            mbar_wait(bars + 8 * (B_FULL + 11));
#pragma unroll
            for (int t = 1; t <= NFAST; t++) stg128(unit(t, warp), make_uint4(0, 0, 0, 0));
        }
        wgmma_wait<0>();
        if (warp == 3) e_arrive(bars + 8 * (B_EMPTY + 10));
    }

    const int w4 = warp & 3;
    __nv_bfloat16* o = ptr_add(out, (uint32_t)(((mt * BM + wg * 128 + w4 * 16 + (lane >> 2)) * F_ + g * BN + (lane & 3) * 8) * 2));
    auto wofs = [](int st, int kk) -> uint32_t {
        return st < 15 ? OFF_W + (st == 11 ? 2 : st == 12 ? 3 : st - 13) * W_BYTES + kk * 2 * CHUNK_BYTES
                       : kk < 2 ? OFF_LUT + kk * 2 * CHUNK_BYTES : OFF_X + 2 * X_BYTES + (kk - 2) * 16384;
    };
    auto xofs = [](int st, int kk, int r) -> uint32_t {
        return (st == 11 ? 2 * X_BYTES + r * 8192 : ((st - 12) >> 1) * X_BYTES + (st & 1) * 8192) + kk * 32;
    };
    auto launder = [&]() { uint32_t b16 = (sbase & 0x3FFFF) >> 4; asm volatile("mov.u32 %0, %0;" : "+r"(b16)); return b16; };
    auto dA = [&](uint32_t b16, uint32_t ofs) { return dscA(b16 + wg * 1024 + (ofs >> 4) + (uint32_t)descA_hi); };
    auto dB = [&](uint32_t b16, uint32_t ofs) { return dscB(b16 + (ofs >> 4) + (uint32_t)descB_hi); };
    {
        mbar_wait(bars + 8 * (B_FULL + 11));
        asm volatile("bar.sync %0, 256;" ::"r"(2 + wg) : "memory");
        const uint32_t b16 = launder();
        wgmma_fence();
#pragma unroll
        for (int kk = 0; kk < 4; kk++) wgmma_m64n224k16(acc0, dA(b16, xofs(11, kk, 0)), dB(b16, wofs(11, kk)), 1);
        wgmma_commit();
        asm volatile("bar.arrive %0, 256;" ::"r"(3 - wg) : "memory");
        if (warp == 7) {
            issue_w(14, 1, B_WF + 2);
            e_expect(bars + 8 * (B_XV + 1), X_BYTES);
            issue_xv(13, 0, bars + 8 * (B_XV + 1)); issue_xv(13, 1, bars + 8 * (B_XV + 1));
            mbar_wait(bars + 8 * (B_EMPTY + 11));
        }
        wgmma_wait<0>();
        if (warp == 3) e_arrive(bars + 8 * (B_EMPTY + 11));
        if (warp == 7) {
            e_bulk(bars + 8 * (B_WF + 4), 2 * CHUNK_BYTES, sbase + wofs(15, 2), wgrp + (15 * 8 + 4) * BN);
            e_bulk(bars + 8 * (B_XV + 4), 2 * CHUNK_BYTES, sbase + wofs(15, 3), wgrp + (15 * 8 + 6) * BN);
        }
    }
    {
        asm volatile("bar.sync %0, 256;" ::"r"(2 + wg) : "memory");
        TSK(0, 28);
        const uint32_t b16 = launder();
#pragma unroll
        for (int st = 12; st < 16; st++) {
            if (!(st & 1)) mbar_wait(bars + 8 * (B_XV + ((st - 12) >> 1)));
            mbar_wait(bars + 8 * (B_WF + st - 12));
            if (!(st & 1)) wgmma_fence();
#pragma unroll
            for (int kk = 0; kk < 4; kk++) {
                if (st == 15 && kk >= 2) mbar_wait(bars + 8 * (kk == 2 ? B_WF + 4 : B_XV + 4));
                wgmma_m64n224k16(acc0, dA(b16, xofs(st, kk, 0)), dB(b16, wofs(st, kk)), 1);
            }
            if (st & 1) wgmma_commit();
        }
        asm volatile("bar.arrive %0, 256;" ::"r"(3 - wg) : "memory");
    }
    float p0[64], p1[32], p2[16];
#pragma unroll
    for (int i = 0; i < 64; i++) asm volatile("add.f32 %0, %1, 0f00000000;" : "=f"(p0[i]) : "f"(acc1[i]));
#pragma unroll
    for (int i = 0; i < 32; i++) asm volatile("add.f32 %0, %1, 0f00000000;" : "=f"(p1[i]) : "f"(acc1[64 + i]));
#pragma unroll
    for (int i = 0; i < 16; i++) asm volatile("add.f32 %0, %1, 0f00000000;" : "=f"(p2[i]) : "f"(acc1[96 + i]));
    wgmma_wait<1>();
    if (w4 == 3) { e_expect(bars + 8 * (B_XV + 2 + wg), X_BYTES / 2); issue_xv(14, wg, bars + 8 * (B_XV + 2 + wg)); }
    wgmma_wait<0>();
    if (w4 == 3) { e_expect(bars + 8 * (B_X15 + wg), X_BYTES / 2); issue_xv(15, wg, bars + 8 * (B_X15 + wg)); }
    TS9(0);
    uint32_t af[80], pk[(14 - CSP) * 4];
    const uint32_t lm = sbase + wg * 16384 + (w4 * 16 + (lane & 15)) * 128 + (((lane >> 4) ^ (lane & 7)) << 4);
    auto ldfrag = [&](int st) {
#pragma unroll
        for (int kk = 0; kk < 4; kk++) {
            uint32_t* r = af + ((st - 11) * 4 + kk) * 4;
            asm volatile("ldmatrix.sync.aligned.m8n8.x4.shared.b16 {%0,%1,%2,%3}, [%4];" : "=r"(r[0]), "=r"(r[1]), "=r"(r[2]), "=r"(r[3])
                         : "r"((lm ^ (kk << 5)) + xofs(st, 0, 1)) : "memory");
        }
    };
    unsigned tb = clk();
#pragma unroll
    for (int h = 0; h < CSP; h++) {
        if (h >= PSF) wait_until(tb, (h - PSF + 1) * PSTA);
        store_half(acc0, o, h);
        if (h == L11) ldfrag(11);
        if (h == L12) { mbar_wait(bars + 8 * (B_XV + 2 + wg)); ldfrag(12); }
    }
#pragma unroll
    for (int h = CSP; h < 14; h++) pack_half(acc0, h, pk + (h - CSP) * 4);
    asm volatile("bar.sync %0, 256;" ::"r"(2 + wg) : "memory");
    uint32_t b16 = launder();
#pragma unroll
    for (int st = 11; st < 16; st++) {
        wgmma_fence();
#pragma unroll
        for (int kk = 0; kk < 4; kk++) {
            const int i = (st - 11) * 4 + kk;
            wgmma_rs(p0, af + i * 4, dB(b16, wofs(st, kk)));
            if (i == 0) TS9(1);
            if (kk == 0 && st < 14) {
                if (st == 12) mbar_wait(bars + 8 * (B_X15 + wg));
                ldfrag(st + 2);
            }
            if (!(i & 1) && CSP + i / 2 < 14) store_packed(o, CSP + i / 2, pk + (i / 2) * 4);
        }
    }
    wgmma_commit();
    asm volatile("bar.arrive %0, 256;" ::"r"(3 - wg) : "memory");
    TS9(2);
    wgmma_wait<0>();
    TS9(3);
    tb = clk();
#pragma unroll
    for (int h = 0; h < DSP; h++) { wait_until(tb, wg ? h * PSTD : PSB0 + h * PSTB); store_half(p0, o + 64 * F_, h); }
    if (wg == 0) {
#pragma unroll
        for (int h = DSP; h < 8; h++) { wait_until(tb, PSB0 + h * PSTB); store_half(p0, o + 64 * F_, h); }
    }
    asm volatile("bar.sync %0, 256;" ::"r"(2 + wg) : "memory");
    b16 = launder();
    wgmma_fence();
#pragma unroll
    for (int i = 0; i < 20; i++) {
        wgmma_rs(p1, af + i * 4, dB(b16, wofs(11 + (i >> 2), i & 3) + 128 * 16));
        if (!(i & 1) && DSP + i / 2 < 8) store_half(p0, o + 64 * F_, DSP + i / 2, wg);
    }
    wgmma_commit();
    asm volatile("bar.arrive %0, 256;" ::"r"(3 - wg) : "memory");
    wgmma_wait<0>();
    TS9(4);
#pragma unroll
    for (int h = 0; h < 4; h++) store_half(p1, o + 64 * F_ + 128, h);
    asm volatile("bar.sync %0, 256;" ::"r"(2 + wg) : "memory");
    wgmma_fence();
#pragma unroll
    for (int i = 0; i < 20; i++) wgmma_rs(p2, af + i * 4, dB(b16, wofs(11 + (i >> 2), i & 3) + 192 * 16));
    wgmma_commit();
    if (wg == 0) asm volatile("bar.arrive 3, 256;" ::: "memory");
    wgmma_wait<0>();
    TSK(4, 63);
    store_half(p2, o + 64 * F_ + 192, 0);
    store_half(p2, o + 64 * F_ + 192, 1);
}

typedef CUresult (*EncodeTiledFn)(CUtensorMap*, CUtensorMapDataType, cuuint32_t, void*, const cuuint64_t*, const cuuint64_t*, const cuuint32_t*, const cuuint32_t*, CUtensorMapInterleave, CUtensorMapSwizzle, CUtensorMapL2promotion, CUtensorMapFloatOOBfill);

extern "C" void kernel_launch(void* const* d_in, const int* in_sizes, int n_in, void* d_out, int out_size) {
    static EncodeTiledFn enc = nullptr;
    static decltype(&fused_kernel<true>) kern = nullptr;
    static void *p_w = nullptr, *p_flags = nullptr, *p_prof = nullptr;
    if (!enc) {
        void* fn = nullptr; cudaDriverEntryPointQueryResult qr;
        cudaGetDriverEntryPoint("cuTensorMapEncodeTiled", &fn, cudaEnableDefault, &qr);
        enc = (EncodeTiledFn)fn;
        int dev = 0, rsv = 0;
        cudaGetDevice(&dev);
        cudaDeviceGetAttribute(&rsv, cudaDevAttrReservedSharedMemoryPerBlock, dev);
        kern = rsv == 1024 && !NOHARD ? fused_kernel<true> : fused_kernel<false>;
        cudaFuncSetAttribute(kern, cudaFuncAttributeMaxDynamicSharedMemorySize, SMEM_BYTES);
        cudaGetSymbolAddress(&p_w, g_w);
        cudaGetSymbolAddress(&p_flags, g_flags);
    }
    CUtensorMap tmx, tmx64, tmq;
    {
        cuuint64_t gdim[2] = {(cuuint64_t)F_, (cuuint64_t)D_};
        cuuint64_t gstr[1] = {(cuuint64_t)F_ * 4};
        cuuint32_t box[2] = {(cuuint32_t)BN, 16};
        cuuint32_t estr[2] = {1, 1};
        enc(&tmq, CU_TENSOR_MAP_DATA_TYPE_INT32, 2, d_in[1], gdim, gstr, box, estr, CU_TENSOR_MAP_INTERLEAVE_NONE,
            CU_TENSOR_MAP_SWIZZLE_NONE, CU_TENSOR_MAP_L2_PROMOTION_L2_128B, CU_TENSOR_MAP_FLOAT_OOB_FILL_NONE);
    }
    {
        cuuint64_t gdim[2] = {(cuuint64_t)D_, (cuuint64_t)S_};
        cuuint64_t gstr[1] = {(cuuint64_t)D_ * 2};
        cuuint32_t box[2] = {(cuuint32_t)BK, (cuuint32_t)BM};
        cuuint32_t estr[2] = {1, 1};
        enc(&tmx, CU_TENSOR_MAP_DATA_TYPE_BFLOAT16, 2, d_in[0], gdim, gstr, box, estr, CU_TENSOR_MAP_INTERLEAVE_NONE,
            CU_TENSOR_MAP_SWIZZLE_128B, CU_TENSOR_MAP_L2_PROMOTION_L2_128B, CU_TENSOR_MAP_FLOAT_OOB_FILL_NONE);
        box[1] = 64;
        enc(&tmx64, CU_TENSOR_MAP_DATA_TYPE_BFLOAT16, 2, d_in[0], gdim, gstr, box, estr, CU_TENSOR_MAP_INTERLEAVE_NONE,
            CU_TENSOR_MAP_SWIZZLE_128B, CU_TENSOR_MAP_L2_PROMOTION_L2_128B, CU_TENSOR_MAP_FLOAT_OOB_FILL_NONE);
    }
    kern<<<128, 256, SMEM_BYTES>>>((const int*)d_in[1], (const unsigned short*)d_in[2], (__nv_bfloat16*)d_out, (uint4*)p_w, (unsigned*)p_flags, tmq, tmx64, tmx
    );
    (void)p_prof;
}
```

```cpp
#include <cuda_runtime.h>
#include <cuda_bf16.h>
#include <cuda.h>
#include <stdint.h>
#include <stdio.h>

#define PR1 1150
#define PX0 950
#define PX0B 2600
#define PR2 2100
#define W1D 260
#define W2D 500
#define W3D 1000
#define R1E 1
#define X1E 0
#define MAP 1
#define PFM 4
#define PFW 8
#define PFE 0
#define NOW 1
#define PSL 0
#define PSL2 0
#define R3A 3
#define R2A 2
#define R4A 0
#define W4L2 0
#define PF0 0
#define PF1 0
#define STM 0
#define STOP ""
#define VG16 0
#define INIT7 1
#define BAL 0
#define SPL 0
#define W1E 0
#define WSH 1
#define WSH2 0
#define W1SH 0
#define X2P 0
#define CSP 10
#define PSTA 110
#define PSF 3
#define L11 3
#define L12 7
#define DSP 4
#define PSB0 150
#define PSTB 110
#define PSTD 100

#define NOHARD 0

constexpr int S_ = 2048, D_ = 1024, F_ = 3584;
constexpr int BM = 256, BN = 224, BK = 64;
constexpr int X_BYTES = BM * BK * 2;
constexpr int W_BYTES = BN * BK * 2;
constexpr int CHUNK_BYTES = BN * 16;
constexpr int SLAB_BYTES = 16 * BN * 4;
constexpr int OFF_X = 0;
constexpr int OFF_W = 3 * X_BYTES;
constexpr int OFF_STG = OFF_W + 3 * W_BYTES;
constexpr int OFF_LUT = OFF_W + 4 * W_BYTES;
constexpr int OFF_BAR = OFF_LUT + 7 * 2048;
constexpr int OFF_PROF = OFF_BAR + 1024;
constexpr int SMEM_BYTES = OFF_PROF + 1024 + 1024;
constexpr int OFF_SLAB0 = OFF_W + 2 * W_BYTES, OFF_SLAB2 = OFF_X + 2 * X_BYTES;
constexpr int B_FULL = 0;
constexpr int B_XV = 12;
constexpr int B_WF = 17;
constexpr int B_EMPTY = 22;
constexpr int B_X0B = 34;
constexpr int B_X15 = 35;
constexpr int B_W1B = 37;
constexpr int B_DQ = 34;
constexpr int B_SLAB = 42;
constexpr int B_LUT = 46;
constexpr int NFAST = 4;
constexpr unsigned long long R_BATCH = 0x60050400ull, W_FLAG = 0x600504000ull;
constexpr unsigned L1_MASK = W4L2 ? 0x2A : 0x2E, L2_MASK = W4L2 ? 0x1EA : 0x1E8;

__device__ __align__(1024) uint4 g_w[(size_t)F_ * D_ / 8];
__device__ __align__(128) unsigned g_flags[16 * 32];

__device__ __forceinline__ uint32_t smem_u32(const void* p) { return (uint32_t)__cvta_generic_to_shared(p); }
__device__ __forceinline__ void mbar_init(uint32_t bar, uint32_t cnt) { asm volatile("mbarrier.init.shared::cta.b64 [%0], %1;" ::"r"(bar), "r"(cnt) : "memory"); }
__device__ __forceinline__ void mbar_wait(uint32_t bar) {
    asm volatile("{\n.reg .pred p;\nWAIT_LOOP:\nmbarrier.try_wait.parity.shared::cta.b64 p, [%0], 0;\n@p bra WAIT_DONE;\nbra WAIT_LOOP;\nWAIT_DONE:\n}" ::"r"(bar) : "memory");
}
__device__ __forceinline__ void e_arrive(uint32_t bar) {
    asm volatile("{\n.reg .pred p;\nelect.sync _|p, 0xffffffff;\n@p mbarrier.arrive.shared::cta.b64 _, [%0];\n}" ::"r"(bar) : "memory");
}
__device__ __forceinline__ void e_expect(uint32_t bar, uint32_t bytes) {
    asm volatile("{\n.reg .pred p;\nelect.sync _|p, 0xffffffff;\n@p mbarrier.arrive.expect_tx.shared::cta.b64 _, [%0], %1;\n}" ::"r"(bar), "r"(bytes) : "memory");
}
__device__ __forceinline__ void e_tma(uint32_t bar, const CUtensorMap* tm, uint32_t d0, int x0, int y0) {
    asm volatile("{\n.reg .pred p;\nelect.sync _|p, 0xffffffff;\n"
                 "@p cp.async.bulk.tensor.2d.shared::cluster.global.mbarrier::complete_tx::bytes [%2], [%1, {%3, %4}], [%0];\n}"
                 ::"r"(bar), "l"(tm), "r"(d0), "r"(x0), "r"(y0) : "memory");
}
__device__ __forceinline__ void e_bulk(uint32_t bar, uint32_t bytes, uint32_t dst, const void* src) {
    asm volatile("{\n.reg .pred p;\nelect.sync _|p, 0xffffffff;\n"
                 "@p mbarrier.arrive.expect_tx.shared::cta.b64 _, [%0], %1;\n"
                 "@p cp.async.bulk.shared::cluster.global.mbarrier::complete_tx::bytes [%2], [%3], %1, [%0];\n}"
                 ::"r"(bar), "r"(bytes), "r"(dst), "l"(src) : "memory");
}
__device__ __forceinline__ void e_bulk_p(uint32_t on, uint32_t bar, uint32_t bytes, uint32_t dst, const void* src) {
    if (on) asm volatile("{\n.reg .pred p;\nelect.sync _|p, 0xffffffff;\n"
                         "@p cp.async.bulk.shared::cluster.global.mbarrier::complete_tx::bytes [%2], [%3], %1, [%0];\n}"
                         ::"r"(bar), "r"(bytes), "r"(dst), "l"(src) : "memory");
}
__device__ __forceinline__ void e_publish(unsigned* flag) {
    asm volatile("{\n.reg .pred p;\nelect.sync _|p, 0xffffffff;\n@p red.release.gpu.global.add.u32 [%0], 1;\n}" ::"l"(flag) : "memory");
}
__device__ __forceinline__ unsigned ld_flag(const unsigned* f) { unsigned v; asm volatile("ld.relaxed.gpu.global.u32 %0, [%1];" : "=r"(v) : "l"(f) : "memory"); return v; }
__device__ __forceinline__ void finish_poll(const unsigned* f, unsigned v, unsigned target) {
    int n = 0;
    while (!__all_sync(0xffffffff, (int)(v - target) >= 0) && ++n < 4000000) v = ld_flag(f);
    asm volatile("fence.acquire.gpu;" ::: "memory");
    asm volatile("fence.proxy.async.global;" ::: "memory");
}
template <typename T> __device__ __forceinline__ T* ptr_add(T* base, uint32_t off) {
    uint64_t r;
    asm("{\n.reg .u32 l, h;\nmov.b64 {l, h}, %1;\nadd.cc.u32 l, l, %2;\naddc.u32 h, h, 0;\nmov.b64 %0, {l, h};\n}" : "=l"(r) : "l"(base), "r"(off));
    return (T*)r;
}
__device__ __forceinline__ void wgmma_fence() { asm volatile("wgmma.fence.sync.aligned;" ::: "memory"); }
__device__ __forceinline__ void wgmma_commit() { asm volatile("wgmma.commit_group.sync.aligned;" ::: "memory"); }
template <int N> __device__ __forceinline__ void wgmma_wait() { asm volatile("wgmma.wait_group.sync.aligned %0;" ::"n"(N) : "memory"); }
__device__ __forceinline__ void wgmma_m64n224k16(float (&d)[112], uint64_t da, uint64_t db, int scale_d) {
    asm volatile(
        "{\n.reg .pred p;\nsetp.ne.b32 p, %114, 0;\n"
        "wgmma.mma_async.sync.aligned.m64n224k16.f32.bf16.bf16 "
        "{%0, %1, %2, %3, %4, %5, %6, %7, %8, %9, %10, %11, %12, %13, %14, %15, "
        "%16, %17, %18, %19, %20, %21, %22, %23, %24, %25, %26, %27, %28, %29, %30, %31, "
        "%32, %33, %34, %35, %36, %37, %38, %39, %40, %41, %42, %43, %44, %45, %46, %47, "
        "%48, %49, %50, %51, %52, %53, %54, %55, %56, %57, %58, %59, %60, %61, %62, %63, "
        "%64, %65, %66, %67, %68, %69, %70, %71, %72, %73, %74, %75, %76, %77, %78, %79, "
        "%80, %81, %82, %83, %84, %85, %86, %87, %88, %89, %90, %91, %92, %93, %94, %95, "
        "%96, %97, %98, %99, %100, %101, %102, %103, %104, %105, %106, %107, %108, %109, %110, %111}, "
        "%112, %113, p, 1, 1, 0, 0;\n}\n"
        : "+f"(d[0]), "+f"(d[1]), "+f"(d[2]), "+f"(d[3]), "+f"(d[4]), "+f"(d[5]), "+f"(d[6]), "+f"(d[7]),
          "+f"(d[8]), "+f"(d[9]), "+f"(d[10]), "+f"(d[11]), "+f"(d[12]), "+f"(d[13]), "+f"(d[14]), "+f"(d[15]),
          "+f"(d[16]), "+f"(d[17]), "+f"(d[18]), "+f"(d[19]), "+f"(d[20]), "+f"(d[21]), "+f"(d[22]), "+f"(d[23]),
          "+f"(d[24]), "+f"(d[25]), "+f"(d[26]), "+f"(d[27]), "+f"(d[28]), "+f"(d[29]), "+f"(d[30]), "+f"(d[31]),
          "+f"(d[32]), "+f"(d[33]), "+f"(d[34]), "+f"(d[35]), "+f"(d[36]), "+f"(d[37]), "+f"(d[38]), "+f"(d[39]),
          "+f"(d[40]), "+f"(d[41]), "+f"(d[42]), "+f"(d[43]), "+f"(d[44]), "+f"(d[45]), "+f"(d[46]), "+f"(d[47]),
          "+f"(d[48]), "+f"(d[49]), "+f"(d[50]), "+f"(d[51]), "+f"(d[52]), "+f"(d[53]), "+f"(d[54]), "+f"(d[55]),
          "+f"(d[56]), "+f"(d[57]), "+f"(d[58]), "+f"(d[59]), "+f"(d[60]), "+f"(d[61]), "+f"(d[62]), "+f"(d[63]),
          "+f"(d[64]), "+f"(d[65]), "+f"(d[66]), "+f"(d[67]), "+f"(d[68]), "+f"(d[69]), "+f"(d[70]), "+f"(d[71]),
          "+f"(d[72]), "+f"(d[73]), "+f"(d[74]), "+f"(d[75]), "+f"(d[76]), "+f"(d[77]), "+f"(d[78]), "+f"(d[79]),
          "+f"(d[80]), "+f"(d[81]), "+f"(d[82]), "+f"(d[83]), "+f"(d[84]), "+f"(d[85]), "+f"(d[86]), "+f"(d[87]),
          "+f"(d[88]), "+f"(d[89]), "+f"(d[90]), "+f"(d[91]), "+f"(d[92]), "+f"(d[93]), "+f"(d[94]), "+f"(d[95]),
          "+f"(d[96]), "+f"(d[97]), "+f"(d[98]), "+f"(d[99]), "+f"(d[100]), "+f"(d[101]), "+f"(d[102]), "+f"(d[103]),
          "+f"(d[104]), "+f"(d[105]), "+f"(d[106]), "+f"(d[107]), "+f"(d[108]), "+f"(d[109]), "+f"(d[110]), "+f"(d[111])
        : "l"(da), "l"(db), "r"(scale_d));
}

__device__ __forceinline__ void wgmma_rs(float (&d)[16], const uint32_t* a, uint64_t db) {
    asm volatile("wgmma.mma_async.sync.aligned.m64n32k16.f32.bf16.bf16 {%0, %1, %2, %3, %4, %5, %6, %7, %8, %9, %10, %11, %12, %13, %14, %15}, {%16, %17, %18, %19}, %20, 1, 1, 1, 0;"
        : "+f"(d[0]), "+f"(d[1]), "+f"(d[2]), "+f"(d[3]), "+f"(d[4]), "+f"(d[5]), "+f"(d[6]), "+f"(d[7]), "+f"(d[8]), "+f"(d[9]), "+f"(d[10]), "+f"(d[11]), "+f"(d[12]), "+f"(d[13]), "+f"(d[14]), "+f"(d[15])
        : "r"(a[0]), "r"(a[1]), "r"(a[2]), "r"(a[3]), "l"(db));
}
__device__ __forceinline__ void wgmma_rs(float (&d)[32], const uint32_t* a, uint64_t db) {
    asm volatile("wgmma.mma_async.sync.aligned.m64n64k16.f32.bf16.bf16 {%0, %1, %2, %3, %4, %5, %6, %7, %8, %9, %10, %11, %12, %13, %14, %15, %16, %17, %18, %19, %20, %21, %22, %23, %24, %25, %26, %27, %28, %29, %30, %31}, {%32, %33, %34, %35}, %36, 1, 1, 1, 0;"
        : "+f"(d[0]), "+f"(d[1]), "+f"(d[2]), "+f"(d[3]), "+f"(d[4]), "+f"(d[5]), "+f"(d[6]), "+f"(d[7]), "+f"(d[8]), "+f"(d[9]), "+f"(d[10]), "+f"(d[11]), "+f"(d[12]), "+f"(d[13]), "+f"(d[14]), "+f"(d[15]), "+f"(d[16]), "+f"(d[17]), "+f"(d[18]), "+f"(d[19]), "+f"(d[20]), "+f"(d[21]), "+f"(d[22]), "+f"(d[23]), "+f"(d[24]), "+f"(d[25]), "+f"(d[26]), "+f"(d[27]), "+f"(d[28]), "+f"(d[29]), "+f"(d[30]), "+f"(d[31])
        : "r"(a[0]), "r"(a[1]), "r"(a[2]), "r"(a[3]), "l"(db));
}
__device__ __forceinline__ void wgmma_rs(float (&d)[64], const uint32_t* a, uint64_t db) {
    asm volatile("wgmma.mma_async.sync.aligned.m64n128k16.f32.bf16.bf16 {%0, %1, %2, %3, %4, %5, %6, %7, %8, %9, %10, %11, %12, %13, %14, %15, %16, %17, %18, %19, %20, %21, %22, %23, %24, %25, %26, %27, %28, %29, %30, %31, %32, %33, %34, %35, %36, %37, %38, %39, %40, %41, %42, %43, %44, %45, %46, %47, %48, %49, %50, %51, %52, %53, %54, %55, %56, %57, %58, %59, %60, %61, %62, %63}, {%64, %65, %66, %67}, %68, 1, 1, 1, 0;"
        : "+f"(d[0]), "+f"(d[1]), "+f"(d[2]), "+f"(d[3]), "+f"(d[4]), "+f"(d[5]), "+f"(d[6]), "+f"(d[7]), "+f"(d[8]), "+f"(d[9]), "+f"(d[10]), "+f"(d[11]), "+f"(d[12]), "+f"(d[13]), "+f"(d[14]), "+f"(d[15]), "+f"(d[16]), "+f"(d[17]), "+f"(d[18]), "+f"(d[19]), "+f"(d[20]), "+f"(d[21]), "+f"(d[22]), "+f"(d[23]), "+f"(d[24]), "+f"(d[25]), "+f"(d[26]), "+f"(d[27]), "+f"(d[28]), "+f"(d[29]), "+f"(d[30]), "+f"(d[31]), "+f"(d[32]), "+f"(d[33]), "+f"(d[34]), "+f"(d[35]), "+f"(d[36]), "+f"(d[37]), "+f"(d[38]), "+f"(d[39]), "+f"(d[40]), "+f"(d[41]), "+f"(d[42]), "+f"(d[43]), "+f"(d[44]), "+f"(d[45]), "+f"(d[46]), "+f"(d[47]), "+f"(d[48]), "+f"(d[49]), "+f"(d[50]), "+f"(d[51]), "+f"(d[52]), "+f"(d[53]), "+f"(d[54]), "+f"(d[55]), "+f"(d[56]), "+f"(d[57]), "+f"(d[58]), "+f"(d[59]), "+f"(d[60]), "+f"(d[61]), "+f"(d[62]), "+f"(d[63])
        : "r"(a[0]), "r"(a[1]), "r"(a[2]), "r"(a[3]), "l"(db));
}

__device__ __forceinline__ uint32_t pack_bf16(float lo, float hi) {
    uint32_t r; asm("cvt.rn.bf16x2.f32 %0, %1, %2;" : "=r"(r) : "f"(hi), "f"(lo)); return r;
}
__device__ __forceinline__ uint32_t lds32(uint32_t a) { uint32_t v; asm volatile("ld.shared.b32 %0, [%1];" : "=r"(v) : "r"(a)); return v; }
__device__ __forceinline__ void sts32(uint32_t a, uint32_t v) { asm volatile("st.shared.b32 [%0], %1;" ::"r"(a), "r"(v) : "memory"); }
__device__ __forceinline__ void sts128(uint32_t a, uint4 v) { asm volatile("st.shared.v4.b32 [%0], {%1,%2,%3,%4};" ::"r"(a), "r"(v.x), "r"(v.y), "r"(v.z), "r"(v.w) : "memory"); }
__device__ __forceinline__ void stg128(void* p, uint4 v) { asm volatile("st.global.v4.b32 [%0], {%1,%2,%3,%4};" ::"l"(p), "r"(v.x), "r"(v.y), "r"(v.z), "r"(v.w) : "memory"); }
__device__ __forceinline__ void cp16(uint32_t dst, const void* src) { asm volatile("cp.async.cg.shared.global [%0], [%1], 16;" ::"r"(dst), "l"(src) : "memory"); }
__device__ __forceinline__ void cp_commit() { asm volatile("cp.async.commit_group;" ::: "memory"); }
template <int N> __device__ __forceinline__ void cp_wait() { asm volatile("cp.async.wait_group %0;" ::"n"(N) : "memory"); }
__device__ __forceinline__ uint4 dequant8(uint32_t raw, uint32_t lut_a) {
    uint32_t v[8];
#pragma unroll
    for (int i = 0; i < 8; i++) v[i] = lds32(raw + i * 128);
#pragma unroll
    for (int i = 0; i < 8; i++) v[i] = lds32(lut_a + v[i] * 128);
    uint4 o;
    o.x = __byte_perm(v[0], v[1], 0x5410); o.y = __byte_perm(v[2], v[3], 0x5410);
    o.z = __byte_perm(v[4], v[5], 0x5410); o.w = __byte_perm(v[6], v[7], 0x5410);
    return o;
}
__device__ __forceinline__ uint32_t prmt(uint32_t a, uint32_t b, uint32_t c) { uint32_t r; asm("prmt.b32 %0, %1, %2, %3;" : "=r"(r) : "r"(a), "r"(b), "r"(c)); return r; }
__device__ __forceinline__ uint4 lookup8_reg(const uint32_t* c, const uint32_t (&T)[8]) {
    uint32_t o[4];
#pragma unroll
    for (int h = 0; h < 2; h++) {
        const uint32_t sel = c[4 * h] + c[4 * h + 1] * 16 + c[4 * h + 2] * 256 + c[4 * h + 3] * 4096;
        const uint32_t s7 = sel & 0x7777u;
        uint32_t m;
        asm("lop3.b32 %0, %1, %2, 0x3210, 0xEA;" : "=r"(m) : "r"(sel >> 1), "r"(0x4444u));
        const uint32_t lo = prmt(prmt(T[0], T[1], s7), prmt(T[2], T[3], s7), m);
        const uint32_t hi = prmt(prmt(T[4], T[5], s7), prmt(T[6], T[7], s7), m);
        o[2 * h] = prmt(lo, hi, 0x5140u); o[2 * h + 1] = prmt(lo, hi, 0x7362u);
    }
    return make_uint4(o[0], o[1], o[2], o[3]);
}
template <int N>
__device__ __forceinline__ void pack_half(const float (&acc)[N], int H, uint32_t* r) {
    const int b = (H >> 1) * 16 + (H & 1) * 2;
#pragma unroll
    for (int i = 0; i < 4; i++) asm volatile("cvt.rn.bf16x2.f32 %0, %1, %2;" : "=r"(r[i]) : "f"(acc[b + 4 * i + 1]), "f"(acc[b + 4 * i]));
}
__device__ __forceinline__ void store_packed(__nv_bfloat16* o, int H, const uint32_t* r, int on = 1) {
    asm volatile("{\n.reg .pred p;\nsetp.ne.b32 p, %5, 0;\n@p st.global" STOP ".v4.b32 [%0], {%1,%2,%3,%4};\n}"
                 ::"l"(o + (H & 1) * 8 * F_ + (H >> 1) * 32), "r"(r[0]), "r"(r[1]), "r"(r[2]), "r"(r[3]), "r"(on) : "memory");
}
template <int N>
__device__ __forceinline__ void store_half(const float (&acc)[N], __nv_bfloat16* o, int H, int on = 1) {
    const int b = (H >> 1) * 16 + (H & 1) * 2;
    const uint32_t r[4] = {pack_bf16(acc[b], acc[b + 1]), pack_bf16(acc[b + 4], acc[b + 5]), pack_bf16(acc[b + 8], acc[b + 9]), pack_bf16(acc[b + 12], acc[b + 13])};
    store_packed(o, H, r, on);
}
template <int V> struct IC { static constexpr int value = V; };
__device__ __forceinline__ unsigned clk() { unsigned c; asm volatile("mov.u32 %0, %%clock;" : "=r"(c)); return c; }
__device__ __forceinline__ void wait_until(unsigned t0, unsigned dt) { while (clk() - t0 < dt) {} }

#define TSK(w, i)
#define TS8(i)
#define TSW(w, i)
#define TS9(i)

template <bool HARD>
__global__ void __launch_bounds__(256, 1)
fused_kernel(const int* __restrict__ qw, const unsigned short* __restrict__ lut, __nv_bfloat16* __restrict__ out,
             uint4* __restrict__ wscr, unsigned* __restrict__ flags,
             const __grid_constant__ CUtensorMap tmq, const __grid_constant__ CUtensorMap tmx64, const __grid_constant__ CUtensorMap tmx
) {
    extern __shared__ uint8_t smem_raw[];
    const uint32_t sbase = HARD ? 1024u : (smem_u32(smem_raw) + 1023) & ~1023u;
    const uint32_t bars = sbase + OFF_BAR;
    const int tid = threadIdx.x, lane = tid & 31;
    const int mt = (blockIdx.x >> 6) * 4 + (blockIdx.x & 3), g = ((blockIdx.x >> 3) & 7) * 2 + ((blockIdx.x >> 2) & 1);
    const unsigned clk0 = clk();
    const int warp = __shfl_sync(0xffffffff, tid >> 5, 0);
    if (tid >= 224) {
        asm volatile("{\n.reg .pred p;\nelect.sync _|p, 0xffffffff;\n"
                     "@p mbarrier.init.shared::cta.b64 [%0], 1;\n"
                     "@p fence.mbarrier_init.release.cluster;\n"
                     "@p mbarrier.arrive.expect_tx.shared::cta.b64 _, [%0], %1;\n"
                     "@p cp.async.bulk.tensor.2d.shared::cluster.global.mbarrier::complete_tx::bytes [%3], [%2, {%4, 0}], [%0];\n}"
                     ::"r"(bars + 8 * B_SLAB), "n"(SLAB_BYTES), "l"(&tmq), "r"(sbase + OFF_SLAB0), "r"(g * BN) : "memory");
    } else {
        const unsigned short* lp = ptr_add(lut, ((lane >> 2) * F_ + g * BN + (tid & ~31) + (lane & 3) * 8) * 2);
        asm volatile("cp.async.cg.shared.global [%0], [%1], 16;\ncp.async.cg.shared.global [%0+512], [%1+57344], 16;\ncp.async.commit_group;"
                     ::"r"(sbase + OFF_STG + (tid >> 5) * 4096 + lane * 16), "l"(lp) : "memory");
    }
    const int sl = warp - 3;
    auto load_slab = [&]() {
        e_tma(bars + 8 * (B_SLAB + sl), &tmq, sbase + (sl < 2 ? OFF_SLAB0 : OFF_SLAB2 - 2 * SLAB_BYTES) + sl * SLAB_BYTES, g * BN, sl * 16);
    };
    if (warp >= 4 && warp < 7) {
        asm volatile("{\n.reg .pred p;\nelect.sync _|p, 0xffffffff;\n"
                     "@p mbarrier.init.shared::cta.b64 [%0], 1;\n"
                     "@p fence.mbarrier_init.release.cluster;\n"
                     "@p mbarrier.arrive.expect_tx.shared::cta.b64 _, [%0], %1;\n}"
                     ::"r"(bars + 8 * (B_SLAB + sl)), "n"(SLAB_BYTES) : "memory");
        if (sl < NOW) load_slab();
    } else if (warp < 2) {
        asm volatile("{\n.reg .pred p;\nelect.sync _|p, 0xffffffff;\n"
                     "@p mbarrier.init.shared::cta.b64 [%0], %1;\n"
                     "@p fence.mbarrier_init.release.cluster;\n}" ::"r"(bars + 8 * (warp ? B_LUT : B_FULL)), "r"(warp ? 7 : 8 + INIT7) : "memory");
    }
    asm volatile("bar.sync 1, 256;" ::: "memory");
    const int wg = warp >> 2;

    const int fl = 8 * ((lane & 7) >> 1) + 2 * (lane >> 3) + (lane & 1);
    const uint32_t lut_a = sbase + OFF_LUT + warp * 2048 + lane * 4;
    const uint32_t stg = sbase + OFF_STG + warp * 4096;
    unsigned* myflags = flags + g * 32;
    const uint4* wgrp = wscr + (size_t)g * 128 * BN;
    unsigned target = 0;

    auto issue_x = [&](int s, int slot) {
        e_tma(bars + 8 * (B_FULL + s), &tmx, sbase + OFF_X + slot * X_BYTES, s * BK, mt * BM);
    };
    auto pf_x = [&](int s) {
        asm volatile("{\n.reg .pred p;\nelect.sync _|p, 0xffffffff;\n@p cp.async.bulk.prefetch.tensor.2d.L2.global [%0, {%1, %2}];\n}"
                     ::"l"(&tmx64), "r"((s + (g >> 2)) * BK), "r"(mt * BM + (g & 3) * 64) : "memory");
    };
    auto issue_xv = [&](int v, int w, uint32_t bar) {
        const uint32_t dst = sbase + OFF_X + (v & 1) * X_BYTES + w * 16384;
        const int k0 = (12 + 2 * (v & 1)) * BK, r0 = mt * BM + w * 128 + ((v >> 1) & 1) * 64;
        e_tma(bar, &tmx64, dst, k0, r0);
        e_tma(bar, &tmx64, dst + 8192, k0 + BK, r0);
    };
    auto issue_w = [&](int s, int slot, int bar) {
        e_bulk(bars + 8 * bar, W_BYTES, sbase + OFF_W + slot * W_BYTES, wgrp + s * 8 * BN);
    };
    auto load_blk = [&](int t, int c) {
        const int* src = ptr_add(qw, (uint32_t)(((t * BK + mt * 8 + (lane >> 3)) * F_ + g * BN + c * 32 + (lane & 7) * 4) * 4));
        asm volatile("cp.async.cg.shared.global [%0], [%1], 16;\ncp.async.cg.shared.global [%0+512], [%1+57344], 16;"
                     ::"r"(sbase + OFF_STG + c * 4096 + (t & 3) * 1024 + lane * 16), "l"(src) : "memory");
    };
    auto load_raw = [&](int t) { if (t < 16) load_blk(t, warp); cp_commit(); };
    auto unit = [&](int t, int c) { return ptr_add(wscr, (uint32_t)(((g * 128 + t * 8 + mt) * BN + c * 32 + lane) * 16)); };
    auto foreign2 = [&]() {
        const int c = warp - 4;
        stg128(unit(2, c), dequant8(sbase + OFF_STG + c * 4096 + 2 * 1024 + fl * 4, sbase + OFF_LUT + c * 2048 + lane * 4));
    };
    auto coop = [&](int t) {
        cp_wait<1>();
        __syncwarp();
        load_raw(t + 2);
        stg128(unit(t, warp), dequant8(stg + (t & 3) * 1024 + fl * 4, lut_a));
    };

    if (warp == 7) {
        if (lane == 0) {
            asm volatile("prefetch.tensormap [%0];" ::"l"(&tmx) : "memory");
            asm volatile("prefetch.tensormap [%0];" ::"l"(&tmx64) : "memory");
        }
        __syncwarp();
        auto x0 = [&](int w, uint32_t bar) {
            e_expect(bar, X_BYTES / 2);
            e_tma(bar, &tmx64, sbase + OFF_X + w * 16384, 0, mt * BM + w * 128);
            e_tma(bar, &tmx64, sbase + OFF_X + w * 16384 + 8192, 0, mt * BM + w * 128 + 64);
        };
        auto inits = [&](int b0, int b1) {
            if (lane == 0) {
#pragma unroll
                for (int b = b0; b < b1; b++) mbar_init(bars + 8 * b, b < B_DQ + 4 ? 1 : 7);
#pragma unroll
                for (int b = b0; b < b1; b++)
                    if (b < B_XV) asm volatile("mbarrier.arrive.expect_tx.shared::cta.b64 _, [%0], %1;" ::"r"(bars + 8 * b), "r"(X_BYTES + (SPL && b == 1 ? W_BYTES / 2 : W_BYTES)) : "memory");
                asm volatile("fence.mbarrier_init.release.cluster;" ::: "memory");
            }
            __syncwarp();
        };
        if (INIT7) inits(1, 9);
        wait_until(clk0, PX0);
        x0(0, bars + 8 * B_FULL);
        if (INIT7) { inits(9, B_SLAB - 1); e_arrive(bars + 8 * B_FULL); }
        auto pf = [&](int k, int row) {
            asm volatile("{\n.reg .pred p;\nelect.sync _|p, 0xffffffff;\n@p cp.async.bulk.prefetch.tensor.2d.L2.global [%0, {%1, %2}];\n}" ::"l"(&tmx64), "r"(k), "r"(row) : "memory");
        };
        if (PF0 && g < 2) { wait_until(clk0, PF0); pf(0, mt * BM + 128 + g * 64); }
        target = ld_flag(myflags + 6);
        wait_until(clk0, PR2);
        load_blk(2, 3);
        cp_commit();
        if (PF1 && (g >> 2) == 1) { wait_until(clk0, PF1); pf(BK, mt * BM + (g & 3) * 64); }
        mbar_wait(bars + 8 * B_LUT);
        wait_until(clk0, PX0B);
        x0(1, bars + 8 * B_X0B);
        target = (target | 7) + 1;
        if (X1E) wait_until(clk0, X1E); else mbar_wait(bars + 8 * B_FULL);
        issue_x(1, 1);
        cp_wait<0>();
        __syncwarp();
        foreign2();
        TSW(7, 3);
    } else {
        if (wg == 1 && sl >= NOW) { if (PSL) wait_until(clk0, PSL + (sl - 2) * PSL2); load_slab(); }
        if (!INIT7 && lane == 0) {
#pragma unroll
            for (int i = 0; i < 6; i++) {
                const int b = 1 + warp * 6 + i;
                if (b < B_SLAB) mbar_init(bars + 8 * b, b < B_DQ + 4 ? 1 : 7);
                if (b < B_XV) asm volatile("mbarrier.arrive.expect_tx.shared::cta.b64 _, [%0], %1;" ::"r"(bars + 8 * b), "r"(X_BYTES + W_BYTES) : "memory");
            }
            asm volatile("fence.mbarrier_init.release.cluster;" ::: "memory");
        }
        __syncwarp();
        wait_until(clk0, PR1);
        load_raw(1);
        uint32_t lv[16], v[32], T[8];
        cp_wait<1>();
        __syncwarp();
#pragma unroll
        for (int i = 0; i < 16; i++) asm volatile("ld.shared.u16 %0, [%1];" : "=r"(lv[i]) : "r"(stg + i * 64 + fl * 2));
#pragma unroll
        for (int i = 0; i < 16; i++) lv[i] = lv[i] ? lv[i] : 0x8000u;
#pragma unroll
        for (int i = 0; i < 4; i++) {
            const uint32_t p01 = prmt(lv[4 * i], lv[4 * i + 1], 0x5140u), p23 = prmt(lv[4 * i + 2], lv[4 * i + 3], 0x5140u);
            T[i] = prmt(p01, p23, 0x5410u); T[4 + i] = prmt(p01, p23, 0x7632u);
        }
        TSW(0, 7);
#pragma unroll
        for (int i = 0; i < 16; i++) sts32(lut_a + i * 128, lv[i]);
        __syncwarp();
        e_arrive(bars + 8 * B_LUT);
        auto own_task = [&](int t) {
            __syncwarp();
            uint32_t c[8];
#pragma unroll
            for (int i = 0; i < 8; i++) c[i] = lds32(stg + t * 1024 + fl * 4 + i * 128);
            stg128(unit(t, warp), lookup8_reg(c, T));
        };
        auto piece_ld = [&](int j) {
            mbar_wait(bars + 8 * (B_SLAB + j));
#pragma unroll
            for (int i = 0; i < 16; i++) v[(j & 1) * 16 + i] = lds32(sbase + (j < 2 ? OFF_SLAB0 : OFF_SLAB2) + (j & 1) * SLAB_BYTES + i * (BN * 4) + (warp * 32 + fl) * 4);
        };
        auto piece_st = [&](int j) {
            const uint32_t dst = sbase + OFF_W + j * 2 * CHUNK_BYTES + (warp * 32 + lane) * 16;
            sts128(dst, lookup8_reg(v + (j & 1) * 16, T));
            sts128(dst + CHUNK_BYTES, lookup8_reg(v + (j & 1) * 16 + 8, T));
            TSW(0, 8 + j);
        };
        if (R2A == 0 && wg == 1) { load_blk(2, warp); load_blk(2, warp - 4); cp_commit(); }
        piece_ld(0);
        if (R2A == 1 && wg == 1) { load_blk(2, warp); load_blk(2, warp - 4); cp_commit(); }
        piece_st(0);
        if (R2A == 2 && wg == 1) { load_blk(2, warp); load_blk(2, warp - 4); cp_commit(); }
        piece_ld(1);
        piece_ld(2);
        if (R3A == 2 && wg == 0) load_raw(3);
        piece_st(1);
        piece_ld(3);
        if (R3A == 3 && wg == 0 && !WSH) load_raw(3);
        if (R1E == 2) { if (wg == 0) cp_wait<1>(); else cp_wait<1>(); own_task(1); }
        piece_st(2);
        if (R1E == 1) { if (WSH && wg == 0) cp_wait<0>(); else cp_wait<1>(); own_task(1); }
        piece_st(3);
        asm volatile("fence.proxy.async.shared::cta;" ::: "memory");
        __syncwarp();
        e_arrive(bars + 8 * B_FULL);
        if (!R1E) { if (R3A == 4 && wg == 0) cp_wait<0>(); else cp_wait<1>(); own_task(1); }
        if (R3A == 4 && wg == 0) load_raw(3);
        TSW(0, 14);
        if (wg == 1) {
            if (!W1SH) load_raw(3);
            if (W1SH) cp_wait<0>(); else cp_wait<1>();
            own_task(2);
            TSW(4, 5);
            if (W1SH == 1) load_raw(3);
            if (R4A == 0 && W1SH < 2) load_raw(4);
            mbar_wait(bars + 8 * B_LUT);
            foreign2();
            if (W1SH == 2) { load_raw(3); load_raw(4); }
            if (R4A == 1) load_raw(4);
        }
        TSW(4, 12);
    }

    float acc0[112], acc1[112];
    const uint64_t descA_hi = ((uint64_t)1 << 62) | ((uint64_t)(1024 >> 4) << 32) | ((uint64_t)1 << 16);
    const uint64_t descB_hi = ((uint64_t)(128 >> 4) << 32) | ((uint64_t)(CHUNK_BYTES >> 4) << 16);
    const uint32_t a16 = ((sbase & 0x3FFFF) >> 4) + wg * 1024 + (uint32_t)descA_hi, b16w = (((sbase + OFF_W) & 0x3FFFF) >> 4) + (uint32_t)descB_hi;
    auto dscA = [&](uint32_t lo) { return (descA_hi & 0xFFFFFFFF00000000ull) | lo; };
    auto dscB = [&](uint32_t lo) { return (descB_hi & 0xFFFFFFFF00000000ull) | lo; };
    uint32_t xo = 0, wo = 0, wo_prev = 2 * W_BYTES;
    const uint4* wnext = wgrp + 2 * 8 * BN;
    auto validate = [&](int t, uint32_t ofs, auto nc) {
        constexpr int LEN = decltype(nc)::value, NB = (LEN + 4095) / 4096;
        const uint32_t a = sbase + OFF_W + wo + ofs;
        for (int n = 0; n < 2000000; n++) {
            uint32_t m = 0xffffffffu;
#pragma unroll
            for (int i = 0; i < NB; i++) m = min(m, lds32(a + tid * 32 + (lane >> 2) * 4 + (i < NB - 1 ? i * 4096 : LEN - 4096)));
            if (__all_sync(0xffffffff, m != 0)) break;
            const uint4* src = ptr_add(wgrp, (uint32_t)((t * 8 * BN + warp * 64 + lane) * 16 + ofs));
#pragma unroll 1
            for (int i = 0; i < 2 * NB; i++) {
                const int u = min((i >> 1) * 256, LEN / 16 - 256) + (i & 1) * 32;
                cp16(a + (warp * 64 + lane + u) * 16, src + u);
            }
            cp_commit();
            cp_wait<0>();
            asm volatile("fence.proxy.async.shared::cta;" ::: "memory");
            __syncwarp();
        }
    };
    auto batch = [&](int s, bool in_loop) {
        mbar_wait(bars + 8 * (B_FULL + s));
        if (!in_loop && s == 0 && wg == 1) { mbar_wait(bars + 8 * B_X0B); TSW(4, 1); }
        if (in_loop && s == 1) TSW(0, 2);
        if (in_loop && wg == 0 && s <= NFAST) {
            if (SPL == 0) validate(s, 0, IC<W_BYTES>());
            else if (SPL == 1) { validate(s, 0, IC<W_BYTES / 2>()); if (s > 1) validate(s, W_BYTES / 2, IC<W_BYTES / 2>()); }
            else validate(s, 0, IC<W_BYTES / 2>());
        }
        if (s + wg > 0) asm volatile("bar.sync %0, 256;" ::"r"(2 + wg) : "memory");
        TSW(0, 16 + s); TSW(4, 48 + s); TS8(16 + s);
        const uint32_t al = a16 + (xo >> 4), bl = b16w + (wo >> 4);
        wgmma_fence();
#pragma unroll
        for (int kk = 0; kk < 4; kk++) {
            if (SPL && in_loop && kk == 2 && (SPL == 1 ? s == 1 : s <= NFAST)) {
                if (s == 1) mbar_wait(bars + 8 * B_W1B);
                if (wg == 0) validate(s, W_BYTES / 2, IC<W_BYTES / 2>());
                wgmma_fence();
            }
            const uint64_t db = dscB(bl + kk * (2 * CHUNK_BYTES >> 4));
            wgmma_m64n224k16(acc0, dscA(al + kk * 2), db, in_loop || (s | kk) != 0);
            wgmma_m64n224k16(acc1, dscA(al + kk * 2 + (8192 >> 4)), db, in_loop || (s | kk) != 0);
        }
        wgmma_commit();
        asm volatile("bar.arrive %0, 256;" ::"r"(3 - wg) : "memory");
        TSW(0, 32 + s); TSW(4, 64 + s);
    };
    auto advance = [&]() {
        wo_prev = wo;
        xo = xo == 2 * X_BYTES ? 0 : xo + X_BYTES;
        wo = wo == 2 * W_BYTES ? 0 : wo + W_BYTES;
        wnext += 8 * BN;
    };
    batch(0, false);
#pragma unroll 1
    for (int s = 0; s < 9; s++) {
        const uint32_t bs = bars + 8 * s;
        if (warp == 7) {
            const int fb = (int)(W_FLAG >> (4 * s)) & 15, pb = (int)(R_BATCH >> (4 * s)) & 15;
            unsigned* fp = ptr_add(myflags, fb * 4);
            unsigned fv = target;
            const uint32_t l1 = (L1_MASK >> s) & 1, l2 = (L2_MASK >> s) & 1;
            if (W3D && s == 1) wait_until(clk(), W3D);
            if (fb) fv = ld_flag(fp);
            else e_bulk_p(l1, bs + 8 * (B_FULL + 2), W_BYTES, sbase + OFF_W + wo_prev, wnext);
            if (s == 0) {
                if (X2P == 0) issue_x(2, 2);
                wait_until(clk(), W2D);
                e_bulk_p(1, bs + 8 * (B_FULL + 2), W_BYTES, sbase + OFF_W + wo_prev, wnext);
                if (X2P == 1) issue_x(2, 2);
            }
            TSW(7, 112 + s);
            if (pb) {
                mbar_wait(bars + 8 * (B_DQ + pb));
                mbar_wait(bs + 8 * B_EMPTY);
                e_publish(ptr_add(myflags, pb * 4));
            } else {
                if (fb) {
                    finish_poll(fp, fv, target);
                    e_bulk_p(l1, bs + 8 * (B_FULL + 2), W_BYTES, sbase + OFF_W + wo_prev, wnext);
                }
                mbar_wait(bs + 8 * B_EMPTY);
                if (s == 8) {
                    issue_w(12, 3, B_WF);
                    e_bulk(bars + 8 * (B_WF + 3), W_BYTES / 2, sbase + OFF_LUT, wgrp + 15 * 8 * BN);
                }
            }
            wgmma_wait<0>();
            if (X2P == 2 && s == 0) issue_x(2, 2);
            e_bulk_p(l2, bs + 8 * (B_FULL + 3), W_BYTES, sbase + OFF_W + wo, wnext + 8 * BN);
            e_tma(bs + 8 * (B_FULL + 3), &tmx, sbase + OFF_X + xo, (s + 3) * BK, mt * BM);
            TSW(7, 96 + s);
        } else {
            const int r = s + wg;
            const unsigned tw = WSH ? clk() : 0;
            if (r == 0) {
                if (!WSH) load_raw(4);
                if (warp == 3) {
                    wait_until(clk(), W1D);
                    e_bulk_p(1, bars + 8 * (B_FULL + 1), SPL ? W_BYTES / 2 : W_BYTES, sbase + OFF_W + W_BYTES, wgrp + 8 * BN);
                    if (SPL) { if (W1E) wait_until(clk(), W1E); e_bulk(bars + 8 * B_W1B, W_BYTES / 2, sbase + OFF_W + W_BYTES + W_BYTES / 2, wgrp + 12 * BN); }
                    TSW(3, 4);
                }
            }
            if (WSH && r == 0) { wait_until(tw, WSH); load_raw(3); wait_until(tw, WSH + WSH2); load_raw(4); }
            else if (!WSH && wg == 0 && s < 2) coop(s + 3);
            else if (r < 8) { coop(2 * r + 1); if (r < 7) coop(2 * r + 2); }
            const int b = (int)(R_BATCH >> (4 * r)) & 15;
            if (b) { __syncwarp(); e_arrive(bars + 8 * (B_DQ + b)); }
            TSW(0, 80 + s);
            wgmma_wait<0>();
            if (warp == 3) e_arrive(bs + 8 * B_EMPTY);
            if (PFM == 1 && warp == 2 && (s & 3) == 1) pf_x(s + 4);
            if (PFM == 2 && warp == 2 && s == 5) pf_x(9);
            if (PFM == 4 && warp == 2 && s == PFW) pf_x(12);
            if (PFM == 4 && PFE && warp == 2 && (s == PFE || s == PFE + 4)) pf_x(s + 8 - PFE - 4);
        }
        advance();
        batch(s + 1, true);
    }
    {
        if (warp == 7) { if (PFM >= 1 && PFM <= 3) pf_x(13); mbar_wait(bars + 8 * (B_EMPTY + 9)); }
        wgmma_wait<0>();
        if (warp == 3) e_arrive(bars + 8 * (B_EMPTY + 9));
        if (warp == 7) {
            issue_w(13, 0, B_WF + 1);
            e_expect(bars + 8 * B_XV, X_BYTES);
            issue_xv(12, 0, bars + 8 * B_XV); issue_xv(12, 1, bars + 8 * B_XV);
        }
        advance();
        batch(10, false);
        if (warp == 7) mbar_wait(bars + 8 * (B_EMPTY + 10));
        else {
            mbar_wait(bars + 8 * (B_FULL + 11));
#pragma unroll
            for (int t = 1; t <= NFAST; t++) stg128(unit(t, warp), make_uint4(0, 0, 0, 0));
        }
        wgmma_wait<0>();
        if (warp == 3) e_arrive(bars + 8 * (B_EMPTY + 10));
    }

    const int w4 = warp & 3;
    __nv_bfloat16* o = ptr_add(out, (uint32_t)(((mt * BM + wg * 128 + w4 * 16 + (lane >> 2)) * F_ + g * BN + (lane & 3) * 8) * 2));
    auto wofs = [](int st, int kk) -> uint32_t {
        return st < 15 ? OFF_W + (st == 11 ? 2 : st == 12 ? 3 : st - 13) * W_BYTES + kk * 2 * CHUNK_BYTES
                       : kk < 2 ? OFF_LUT + kk * 2 * CHUNK_BYTES : OFF_X + 2 * X_BYTES + (kk - 2) * 16384;
    };
    auto xofs = [](int st, int kk, int r) -> uint32_t {
        return (st == 11 ? 2 * X_BYTES + r * 8192 : ((st - 12) >> 1) * X_BYTES + (st & 1) * 8192) + kk * 32;
    };
    auto launder = [&]() { uint32_t b16 = (sbase & 0x3FFFF) >> 4; asm volatile("mov.u32 %0, %0;" : "+r"(b16)); return b16; };
    auto dA = [&](uint32_t b16, uint32_t ofs) { return dscA(b16 + wg * 1024 + (ofs >> 4) + (uint32_t)descA_hi); };
    auto dB = [&](uint32_t b16, uint32_t ofs) { return dscB(b16 + (ofs >> 4) + (uint32_t)descB_hi); };
    {
        mbar_wait(bars + 8 * (B_FULL + 11));
        asm volatile("bar.sync %0, 256;" ::"r"(2 + wg) : "memory");
        const uint32_t b16 = launder();
        wgmma_fence();
#pragma unroll
        for (int kk = 0; kk < 4; kk++) wgmma_m64n224k16(acc0, dA(b16, xofs(11, kk, 0)), dB(b16, wofs(11, kk)), 1);
        wgmma_commit();
        asm volatile("bar.arrive %0, 256;" ::"r"(3 - wg) : "memory");
        if (warp == 7) {
            issue_w(14, 1, B_WF + 2);
            e_expect(bars + 8 * (B_XV + 1), X_BYTES);
            issue_xv(13, 0, bars + 8 * (B_XV + 1)); issue_xv(13, 1, bars + 8 * (B_XV + 1));
            mbar_wait(bars + 8 * (B_EMPTY + 11));
        }
        wgmma_wait<0>();
        if (warp == 3) e_arrive(bars + 8 * (B_EMPTY + 11));
        if (warp == 7) {
            e_bulk(bars + 8 * (B_WF + 4), 2 * CHUNK_BYTES, sbase + wofs(15, 2), wgrp + (15 * 8 + 4) * BN);
            e_bulk(bars + 8 * (B_XV + 4), 2 * CHUNK_BYTES, sbase + wofs(15, 3), wgrp + (15 * 8 + 6) * BN);
        }
    }
    {
        asm volatile("bar.sync %0, 256;" ::"r"(2 + wg) : "memory");
        TSK(0, 28);
        const uint32_t b16 = launder();
#pragma unroll
        for (int st = 12; st < 16; st++) {
            if (!(st & 1)) mbar_wait(bars + 8 * (B_XV + ((st - 12) >> 1)));
            mbar_wait(bars + 8 * (B_WF + st - 12));
            if (!(st & 1)) wgmma_fence();
#pragma unroll
            for (int kk = 0; kk < 4; kk++) {
                if (st == 15 && kk >= 2) mbar_wait(bars + 8 * (kk == 2 ? B_WF + 4 : B_XV + 4));
                wgmma_m64n224k16(acc0, dA(b16, xofs(st, kk, 0)), dB(b16, wofs(st, kk)), 1);
            }
            if (st & 1) wgmma_commit();
        }
        asm volatile("bar.arrive %0, 256;" ::"r"(3 - wg) : "memory");
    }
    float p0[64], p1[32], p2[16];
#pragma unroll
    for (int i = 0; i < 64; i++) asm volatile("add.f32 %0, %1, 0f00000000;" : "=f"(p0[i]) : "f"(acc1[i]));
#pragma unroll
    for (int i = 0; i < 32; i++) asm volatile("add.f32 %0, %1, 0f00000000;" : "=f"(p1[i]) : "f"(acc1[64 + i]));
#pragma unroll
    for (int i = 0; i < 16; i++) asm volatile("add.f32 %0, %1, 0f00000000;" : "=f"(p2[i]) : "f"(acc1[96 + i]));
    wgmma_wait<1>();
    if (w4 == 3) { e_expect(bars + 8 * (B_XV + 2 + wg), X_BYTES / 2); issue_xv(14, wg, bars + 8 * (B_XV + 2 + wg)); }
    wgmma_wait<0>();
    if (w4 == 3) { e_expect(bars + 8 * (B_X15 + wg), X_BYTES / 2); issue_xv(15, wg, bars + 8 * (B_X15 + wg)); }
    TS9(0);
    uint32_t af[80], pk[(14 - CSP) * 4];
    const uint32_t lm = sbase + wg * 16384 + (w4 * 16 + (lane & 15)) * 128 + (((lane >> 4) ^ (lane & 7)) << 4);
    auto ldfrag = [&](int st) {
#pragma unroll
        for (int kk = 0; kk < 4; kk++) {
            uint32_t* r = af + ((st - 11) * 4 + kk) * 4;
            asm volatile("ldmatrix.sync.aligned.m8n8.x4.shared.b16 {%0,%1,%2,%3}, [%4];" : "=r"(r[0]), "=r"(r[1]), "=r"(r[2]), "=r"(r[3])
                         : "r"((lm ^ (kk << 5)) + xofs(st, 0, 1)) : "memory");
        }
    };
    unsigned tb = clk();
#pragma unroll
    for (int h = 0; h < CSP; h++) {
        if (h >= PSF) wait_until(tb, (h - PSF + 1) * PSTA);
        store_half(acc0, o, h);
        if (h == L11) ldfrag(11);
        if (h == L12) { mbar_wait(bars + 8 * (B_XV + 2 + wg)); ldfrag(12); }
    }
#pragma unroll
    for (int h = CSP; h < 14; h++) pack_half(acc0, h, pk + (h - CSP) * 4);
    asm volatile("bar.sync %0, 256;" ::"r"(2 + wg) : "memory");
    uint32_t b16 = launder();
#pragma unroll
    for (int st = 11; st < 16; st++) {
        wgmma_fence();
#pragma unroll
        for (int kk = 0; kk < 4; kk++) {
            const int i = (st - 11) * 4 + kk;
            wgmma_rs(p0, af + i * 4, dB(b16, wofs(st, kk)));
            if (i == 0) TS9(1);
            if (kk == 0 && st < 14) {
                if (st == 12) mbar_wait(bars + 8 * (B_X15 + wg));
                ldfrag(st + 2);
            }
            if (!(i & 1) && CSP + i / 2 < 14) store_packed(o, CSP + i / 2, pk + (i / 2) * 4);
        }
    }
    wgmma_commit();
    asm volatile("bar.arrive %0, 256;" ::"r"(3 - wg) : "memory");
    TS9(2);
    wgmma_wait<0>();
    TS9(3);
    tb = clk();
#pragma unroll
    for (int h = 0; h < DSP; h++) { wait_until(tb, wg ? h * PSTD : PSB0 + h * PSTB); store_half(p0, o + 64 * F_, h); }
    if (wg == 0) {
#pragma unroll
        for (int h = DSP; h < 8; h++) { wait_until(tb, PSB0 + h * PSTB); store_half(p0, o + 64 * F_, h); }
    }
    asm volatile("bar.sync %0, 256;" ::"r"(2 + wg) : "memory");
    b16 = launder();
    wgmma_fence();
#pragma unroll
    for (int i = 0; i < 20; i++) {
        wgmma_rs(p1, af + i * 4, dB(b16, wofs(11 + (i >> 2), i & 3) + 128 * 16));
        if (!(i & 1) && DSP + i / 2 < 8) store_half(p0, o + 64 * F_, DSP + i / 2, wg);
    }
    wgmma_commit();
    asm volatile("bar.arrive %0, 256;" ::"r"(3 - wg) : "memory");
    wgmma_wait<0>();
    TS9(4);
#pragma unroll
    for (int h = 0; h < 4; h++) store_half(p1, o + 64 * F_ + 128, h);
    asm volatile("bar.sync %0, 256;" ::"r"(2 + wg) : "memory");
    wgmma_fence();
#pragma unroll
    for (int i = 0; i < 20; i++) wgmma_rs(p2, af + i * 4, dB(b16, wofs(11 + (i >> 2), i & 3) + 192 * 16));
    wgmma_commit();
    if (wg == 0) asm volatile("bar.arrive 3, 256;" ::: "memory");
    wgmma_wait<0>();
    TSK(4, 63);
    store_half(p2, o + 64 * F_ + 192, 0);
    store_half(p2, o + 64 * F_ + 192, 1);
}

typedef CUresult (*EncodeTiledFn)(CUtensorMap*, CUtensorMapDataType, cuuint32_t, void*, const cuuint64_t*, const cuuint64_t*, const cuuint32_t*, const cuuint32_t*, CUtensorMapInterleave, CUtensorMapSwizzle, CUtensorMapL2promotion, CUtensorMapFloatOOBfill);

extern "C" void kernel_launch(void* const* d_in, const int* in_sizes, int n_in, void* d_out, int out_size) {
    static EncodeTiledFn enc = nullptr;
    static decltype(&fused_kernel<true>) kern = nullptr;
    static void *p_w = nullptr, *p_flags = nullptr, *p_prof = nullptr;
    if (!enc) {
        void* fn = nullptr; cudaDriverEntryPointQueryResult qr;
        cudaGetDriverEntryPoint("cuTensorMapEncodeTiled", &fn, cudaEnableDefault, &qr);
        enc = (EncodeTiledFn)fn;
        int dev = 0, rsv = 0;
        cudaGetDevice(&dev);
        cudaDeviceGetAttribute(&rsv, cudaDevAttrReservedSharedMemoryPerBlock, dev);
        kern = rsv == 1024 && !NOHARD ? fused_kernel<true> : fused_kernel<false>;
        cudaFuncSetAttribute(kern, cudaFuncAttributeMaxDynamicSharedMemorySize, SMEM_BYTES);
        cudaGetSymbolAddress(&p_w, g_w);
        cudaGetSymbolAddress(&p_flags, g_flags);
    }
    CUtensorMap tmx, tmx64, tmq;
    {
        cuuint64_t gdim[2] = {(cuuint64_t)F_, (cuuint64_t)D_};
        cuuint64_t gstr[1] = {(cuuint64_t)F_ * 4};
        cuuint32_t box[2] = {(cuuint32_t)BN, 16};
        cuuint32_t estr[2] = {1, 1};
        enc(&tmq, CU_TENSOR_MAP_DATA_TYPE_INT32, 2, d_in[1], gdim, gstr, box, estr, CU_TENSOR_MAP_INTERLEAVE_NONE,
            CU_TENSOR_MAP_SWIZZLE_NONE, CU_TENSOR_MAP_L2_PROMOTION_L2_128B, CU_TENSOR_MAP_FLOAT_OOB_FILL_NONE);
    }
    {
        cuuint64_t gdim[2] = {(cuuint64_t)D_, (cuuint64_t)S_};
        cuuint64_t gstr[1] = {(cuuint64_t)D_ * 2};
        cuuint32_t box[2] = {(cuuint32_t)BK, (cuuint32_t)BM};
        cuuint32_t estr[2] = {1, 1};
        enc(&tmx, CU_TENSOR_MAP_DATA_TYPE_BFLOAT16, 2, d_in[0], gdim, gstr, box, estr, CU_TENSOR_MAP_INTERLEAVE_NONE,
            CU_TENSOR_MAP_SWIZZLE_128B, CU_TENSOR_MAP_L2_PROMOTION_L2_128B, CU_TENSOR_MAP_FLOAT_OOB_FILL_NONE);
        box[1] = 64;
        enc(&tmx64, CU_TENSOR_MAP_DATA_TYPE_BFLOAT16, 2, d_in[0], gdim, gstr, box, estr, CU_TENSOR_MAP_INTERLEAVE_NONE,
            CU_TENSOR_MAP_SWIZZLE_128B, CU_TENSOR_MAP_L2_PROMOTION_L2_128B, CU_TENSOR_MAP_FLOAT_OOB_FILL_NONE);
    }
    kern<<<128, 256, SMEM_BYTES>>>((const int*)d_in[1], (const unsigned short*)d_in[2], (__nv_bfloat16*)d_out, (uint4*)p_w, (unsigned*)p_flags, tmq, tmx64, tmx
    );
    (void)p_prof;
}
```

```cpp
#include <cuda_runtime.h>
#include <cuda_bf16.h>
#include <cuda.h>
#include <stdint.h>
#include <stdio.h>

#define PR1 1150
#define PX0 950
#define PX0B 2600
#define PR2 2100
#define W1D 260
#define W2D 500
#define W3D 1000
#define CSP 10
#define PSTA 110
#define PSF 3
#define L11 4
#define L12 7
#define DSP 4
#define PSB0 150
#define PSTB 110
#define PSTD 100

#define NOHARD 0

constexpr int S_ = 2048, D_ = 1024, F_ = 3584;
constexpr int BM = 256, BN = 224, BK = 64;
constexpr int X_BYTES = BM * BK * 2;
constexpr int W_BYTES = BN * BK * 2;
constexpr int CHUNK_BYTES = BN * 16;
constexpr int SLAB_BYTES = 16 * BN * 4;
constexpr int OFF_X = 0;
constexpr int OFF_W = 3 * X_BYTES;
constexpr int OFF_STG = OFF_W + 3 * W_BYTES;
constexpr int OFF_LUT = OFF_W + 4 * W_BYTES;
constexpr int OFF_BAR = OFF_LUT + 7 * 2048;
constexpr int OFF_PROF = OFF_BAR + 1024;
constexpr int SMEM_BYTES = OFF_PROF + 1024 + 1024;
constexpr int OFF_SLAB0 = OFF_W + 2 * W_BYTES, OFF_SLAB2 = OFF_X + 2 * X_BYTES;
constexpr int B_FULL = 0;
constexpr int B_XV = 12;
constexpr int B_WF = 17;
constexpr int B_EMPTY = 22;
constexpr int B_X0B = 34;
constexpr int B_X15 = 35;
constexpr int B_DQ = 34;
constexpr int B_SLAB = 42;
constexpr int B_LUT = 46;
constexpr int NFAST = 4;
constexpr unsigned long long R_BATCH = 0x60050400ull, W_FLAG = 0x600504000ull;
constexpr unsigned L1_MASK = 0x2E, L2_MASK = 0x1E8;

__device__ __align__(1024) uint4 g_w[(size_t)F_ * D_ / 8];
__device__ __align__(128) unsigned g_flags[16 * 32];

__device__ __forceinline__ uint32_t smem_u32(const void* p) { return (uint32_t)__cvta_generic_to_shared(p); }
__device__ __forceinline__ void mbar_init(uint32_t bar, uint32_t cnt) { asm volatile("mbarrier.init.shared::cta.b64 [%0], %1;" ::"r"(bar), "r"(cnt) : "memory"); }
__device__ __forceinline__ void mbar_wait(uint32_t bar) {
    asm volatile("{\n.reg .pred p;\nWAIT_LOOP:\nmbarrier.try_wait.parity.shared::cta.b64 p, [%0], 0;\n@p bra WAIT_DONE;\nbra WAIT_LOOP;\nWAIT_DONE:\n}" ::"r"(bar) : "memory");
}
__device__ __forceinline__ void e_arrive(uint32_t bar) {
    asm volatile("{\n.reg .pred p;\nelect.sync _|p, 0xffffffff;\n@p mbarrier.arrive.shared::cta.b64 _, [%0];\n}" ::"r"(bar) : "memory");
}
__device__ __forceinline__ void e_expect(uint32_t bar, uint32_t bytes) {
    asm volatile("{\n.reg .pred p;\nelect.sync _|p, 0xffffffff;\n@p mbarrier.arrive.expect_tx.shared::cta.b64 _, [%0], %1;\n}" ::"r"(bar), "r"(bytes) : "memory");
}
__device__ __forceinline__ void e_tma(uint32_t bar, const CUtensorMap* tm, uint32_t d0, int x0, int y0) {
    asm volatile("{\n.reg .pred p;\nelect.sync _|p, 0xffffffff;\n"
                 "@p cp.async.bulk.tensor.2d.shared::cluster.global.mbarrier::complete_tx::bytes [%2], [%1, {%3, %4}], [%0];\n}"
                 ::"r"(bar), "l"(tm), "r"(d0), "r"(x0), "r"(y0) : "memory");
}
__device__ __forceinline__ void e_bulk(uint32_t bar, uint32_t bytes, uint32_t dst, const void* src) {
    asm volatile("{\n.reg .pred p;\nelect.sync _|p, 0xffffffff;\n"
                 "@p mbarrier.arrive.expect_tx.shared::cta.b64 _, [%0], %1;\n"
                 "@p cp.async.bulk.shared::cluster.global.mbarrier::complete_tx::bytes [%2], [%3], %1, [%0];\n}"
                 ::"r"(bar), "r"(bytes), "r"(dst), "l"(src) : "memory");
}
__device__ __forceinline__ void e_bulk_p(uint32_t on, uint32_t bar, uint32_t bytes, uint32_t dst, const void* src) {
    if (on) asm volatile("{\n.reg .pred p;\nelect.sync _|p, 0xffffffff;\n"
                         "@p cp.async.bulk.shared::cluster.global.mbarrier::complete_tx::bytes [%2], [%3], %1, [%0];\n}"
                         ::"r"(bar), "r"(bytes), "r"(dst), "l"(src) : "memory");
}
__device__ __forceinline__ void e_publish(unsigned* flag) {
    asm volatile("{\n.reg .pred p;\nelect.sync _|p, 0xffffffff;\n@p red.release.gpu.global.add.u32 [%0], 1;\n}" ::"l"(flag) : "memory");
}
__device__ __forceinline__ unsigned ld_flag(const unsigned* f) { unsigned v; asm volatile("ld.relaxed.gpu.global.u32 %0, [%1];" : "=r"(v) : "l"(f) : "memory"); return v; }
__device__ __forceinline__ void finish_poll(const unsigned* f, unsigned v, unsigned target) {
    int n = 0;
    while (!__all_sync(0xffffffff, (int)(v - target) >= 0) && ++n < 4000000) v = ld_flag(f);
    asm volatile("fence.acquire.gpu;" ::: "memory");
    asm volatile("fence.proxy.async.global;" ::: "memory");
}
template <typename T> __device__ __forceinline__ T* ptr_add(T* base, uint32_t off) {
    uint64_t r;
    asm("{\n.reg .u32 l, h;\nmov.b64 {l, h}, %1;\nadd.cc.u32 l, l, %2;\naddc.u32 h, h, 0;\nmov.b64 %0, {l, h};\n}" : "=l"(r) : "l"(base), "r"(off));
    return (T*)r;
}
__device__ __forceinline__ void wgmma_fence() { asm volatile("wgmma.fence.sync.aligned;" ::: "memory"); }
__device__ __forceinline__ void wgmma_commit() { asm volatile("wgmma.commit_group.sync.aligned;" ::: "memory"); }
template <int N> __device__ __forceinline__ void wgmma_wait() { asm volatile("wgmma.wait_group.sync.aligned %0;" ::"n"(N) : "memory"); }
__device__ __forceinline__ void wgmma_m64n224k16(float (&d)[112], uint64_t da, uint64_t db, int scale_d) {
    asm volatile(
        "{\n.reg .pred p;\nsetp.ne.b32 p, %114, 0;\n"
        "wgmma.mma_async.sync.aligned.m64n224k16.f32.bf16.bf16 "
        "{%0, %1, %2, %3, %4, %5, %6, %7, %8, %9, %10, %11, %12, %13, %14, %15, "
        "%16, %17, %18, %19, %20, %21, %22, %23, %24, %25, %26, %27, %28, %29, %30, %31, "
        "%32, %33, %34, %35, %36, %37, %38, %39, %40, %41, %42, %43, %44, %45, %46, %47, "
        "%48, %49, %50, %51, %52, %53, %54, %55, %56, %57, %58, %59, %60, %61, %62, %63, "
        "%64, %65, %66, %67, %68, %69, %70, %71, %72, %73, %74, %75, %76, %77, %78, %79, "
        "%80, %81, %82, %83, %84, %85, %86, %87, %88, %89, %90, %91, %92, %93, %94, %95, "
        "%96, %97, %98, %99, %100, %101, %102, %103, %104, %105, %106, %107, %108, %109, %110, %111}, "
        "%112, %113, p, 1, 1, 0, 0;\n}\n"
        : "+f"(d[0]), "+f"(d[1]), "+f"(d[2]), "+f"(d[3]), "+f"(d[4]), "+f"(d[5]), "+f"(d[6]), "+f"(d[7]),
          "+f"(d[8]), "+f"(d[9]), "+f"(d[10]), "+f"(d[11]), "+f"(d[12]), "+f"(d[13]), "+f"(d[14]), "+f"(d[15]),
          "+f"(d[16]), "+f"(d[17]), "+f"(d[18]), "+f"(d[19]), "+f"(d[20]), "+f"(d[21]), "+f"(d[22]), "+f"(d[23]),
          "+f"(d[24]), "+f"(d[25]), "+f"(d[26]), "+f"(d[27]), "+f"(d[28]), "+f"(d[29]), "+f"(d[30]), "+f"(d[31]),
          "+f"(d[32]), "+f"(d[33]), "+f"(d[34]), "+f"(d[35]), "+f"(d[36]), "+f"(d[37]), "+f"(d[38]), "+f"(d[39]),
          "+f"(d[40]), "+f"(d[41]), "+f"(d[42]), "+f"(d[43]), "+f"(d[44]), "+f"(d[45]), "+f"(d[46]), "+f"(d[47]),
          "+f"(d[48]), "+f"(d[49]), "+f"(d[50]), "+f"(d[51]), "+f"(d[52]), "+f"(d[53]), "+f"(d[54]), "+f"(d[55]),
          "+f"(d[56]), "+f"(d[57]), "+f"(d[58]), "+f"(d[59]), "+f"(d[60]), "+f"(d[61]), "+f"(d[62]), "+f"(d[63]),
          "+f"(d[64]), "+f"(d[65]), "+f"(d[66]), "+f"(d[67]), "+f"(d[68]), "+f"(d[69]), "+f"(d[70]), "+f"(d[71]),
          "+f"(d[72]), "+f"(d[73]), "+f"(d[74]), "+f"(d[75]), "+f"(d[76]), "+f"(d[77]), "+f"(d[78]), "+f"(d[79]),
          "+f"(d[80]), "+f"(d[81]), "+f"(d[82]), "+f"(d[83]), "+f"(d[84]), "+f"(d[85]), "+f"(d[86]), "+f"(d[87]),
          "+f"(d[88]), "+f"(d[89]), "+f"(d[90]), "+f"(d[91]), "+f"(d[92]), "+f"(d[93]), "+f"(d[94]), "+f"(d[95]),
          "+f"(d[96]), "+f"(d[97]), "+f"(d[98]), "+f"(d[99]), "+f"(d[100]), "+f"(d[101]), "+f"(d[102]), "+f"(d[103]),
          "+f"(d[104]), "+f"(d[105]), "+f"(d[106]), "+f"(d[107]), "+f"(d[108]), "+f"(d[109]), "+f"(d[110]), "+f"(d[111])
        : "l"(da), "l"(db), "r"(scale_d));
}

__device__ __forceinline__ void wgmma_rs(float (&d)[16], const uint32_t* a, uint64_t db) {
    asm volatile("wgmma.mma_async.sync.aligned.m64n32k16.f32.bf16.bf16 {%0, %1, %2, %3, %4, %5, %6, %7, %8, %9, %10, %11, %12, %13, %14, %15}, {%16, %17, %18, %19}, %20, 1, 1, 1, 0;"
        : "+f"(d[0]), "+f"(d[1]), "+f"(d[2]), "+f"(d[3]), "+f"(d[4]), "+f"(d[5]), "+f"(d[6]), "+f"(d[7]), "+f"(d[8]), "+f"(d[9]), "+f"(d[10]), "+f"(d[11]), "+f"(d[12]), "+f"(d[13]), "+f"(d[14]), "+f"(d[15])
        : "r"(a[0]), "r"(a[1]), "r"(a[2]), "r"(a[3]), "l"(db));
}
__device__ __forceinline__ void wgmma_rs(float (&d)[32], const uint32_t* a, uint64_t db) {
    asm volatile("wgmma.mma_async.sync.aligned.m64n64k16.f32.bf16.bf16 {%0, %1, %2, %3, %4, %5, %6, %7, %8, %9, %10, %11, %12, %13, %14, %15, %16, %17, %18, %19, %20, %21, %22, %23, %24, %25, %26, %27, %28, %29, %30, %31}, {%32, %33, %34, %35}, %36, 1, 1, 1, 0;"
        : "+f"(d[0]), "+f"(d[1]), "+f"(d[2]), "+f"(d[3]), "+f"(d[4]), "+f"(d[5]), "+f"(d[6]), "+f"(d[7]), "+f"(d[8]), "+f"(d[9]), "+f"(d[10]), "+f"(d[11]), "+f"(d[12]), "+f"(d[13]), "+f"(d[14]), "+f"(d[15]), "+f"(d[16]), "+f"(d[17]), "+f"(d[18]), "+f"(d[19]), "+f"(d[20]), "+f"(d[21]), "+f"(d[22]), "+f"(d[23]), "+f"(d[24]), "+f"(d[25]), "+f"(d[26]), "+f"(d[27]), "+f"(d[28]), "+f"(d[29]), "+f"(d[30]), "+f"(d[31])
        : "r"(a[0]), "r"(a[1]), "r"(a[2]), "r"(a[3]), "l"(db));
}
__device__ __forceinline__ void wgmma_rs(float (&d)[64], const uint32_t* a, uint64_t db) {
    asm volatile("wgmma.mma_async.sync.aligned.m64n128k16.f32.bf16.bf16 {%0, %1, %2, %3, %4, %5, %6, %7, %8, %9, %10, %11, %12, %13, %14, %15, %16, %17, %18, %19, %20, %21, %22, %23, %24, %25, %26, %27, %28, %29, %30, %31, %32, %33, %34, %35, %36, %37, %38, %39, %40, %41, %42, %43, %44, %45, %46, %47, %48, %49, %50, %51, %52, %53, %54, %55, %56, %57, %58, %59, %60, %61, %62, %63}, {%64, %65, %66, %67}, %68, 1, 1, 1, 0;"
        : "+f"(d[0]), "+f"(d[1]), "+f"(d[2]), "+f"(d[3]), "+f"(d[4]), "+f"(d[5]), "+f"(d[6]), "+f"(d[7]), "+f"(d[8]), "+f"(d[9]), "+f"(d[10]), "+f"(d[11]), "+f"(d[12]), "+f"(d[13]), "+f"(d[14]), "+f"(d[15]), "+f"(d[16]), "+f"(d[17]), "+f"(d[18]), "+f"(d[19]), "+f"(d[20]), "+f"(d[21]), "+f"(d[22]), "+f"(d[23]), "+f"(d[24]), "+f"(d[25]), "+f"(d[26]), "+f"(d[27]), "+f"(d[28]), "+f"(d[29]), "+f"(d[30]), "+f"(d[31]), "+f"(d[32]), "+f"(d[33]), "+f"(d[34]), "+f"(d[35]), "+f"(d[36]), "+f"(d[37]), "+f"(d[38]), "+f"(d[39]), "+f"(d[40]), "+f"(d[41]), "+f"(d[42]), "+f"(d[43]), "+f"(d[44]), "+f"(d[45]), "+f"(d[46]), "+f"(d[47]), "+f"(d[48]), "+f"(d[49]), "+f"(d[50]), "+f"(d[51]), "+f"(d[52]), "+f"(d[53]), "+f"(d[54]), "+f"(d[55]), "+f"(d[56]), "+f"(d[57]), "+f"(d[58]), "+f"(d[59]), "+f"(d[60]), "+f"(d[61]), "+f"(d[62]), "+f"(d[63])
        : "r"(a[0]), "r"(a[1]), "r"(a[2]), "r"(a[3]), "l"(db));
}

__device__ __forceinline__ uint32_t pack_bf16(float lo, float hi) {
    uint32_t r; asm("cvt.rn.bf16x2.f32 %0, %1, %2;" : "=r"(r) : "f"(hi), "f"(lo)); return r;
}
__device__ __forceinline__ uint32_t lds32(uint32_t a) { uint32_t v; asm volatile("ld.shared.b32 %0, [%1];" : "=r"(v) : "r"(a)); return v; }
__device__ __forceinline__ void sts32(uint32_t a, uint32_t v) { asm volatile("st.shared.b32 [%0], %1;" ::"r"(a), "r"(v) : "memory"); }
__device__ __forceinline__ void sts128(uint32_t a, uint4 v) { asm volatile("st.shared.v4.b32 [%0], {%1,%2,%3,%4};" ::"r"(a), "r"(v.x), "r"(v.y), "r"(v.z), "r"(v.w) : "memory"); }
__device__ __forceinline__ void stg128(void* p, uint4 v) { asm volatile("st.global.v4.b32 [%0], {%1,%2,%3,%4};" ::"l"(p), "r"(v.x), "r"(v.y), "r"(v.z), "r"(v.w) : "memory"); }
__device__ __forceinline__ void cp16(uint32_t dst, const void* src) { asm volatile("cp.async.cg.shared.global [%0], [%1], 16;" ::"r"(dst), "l"(src) : "memory"); }
__device__ __forceinline__ void cp_commit() { asm volatile("cp.async.commit_group;" ::: "memory"); }
template <int N> __device__ __forceinline__ void cp_wait() { asm volatile("cp.async.wait_group %0;" ::"n"(N) : "memory"); }
__device__ __forceinline__ uint4 dequant8(uint32_t raw, uint32_t lut_a) {
    uint32_t v[8];
#pragma unroll
    for (int i = 0; i < 8; i++) v[i] = lds32(raw + i * 128);
#pragma unroll
    for (int i = 0; i < 8; i++) v[i] = lds32(lut_a + v[i] * 128);
    uint4 o;
    o.x = __byte_perm(v[0], v[1], 0x5410); o.y = __byte_perm(v[2], v[3], 0x5410);
    o.z = __byte_perm(v[4], v[5], 0x5410); o.w = __byte_perm(v[6], v[7], 0x5410);
    return o;
}
__device__ __forceinline__ uint32_t prmt(uint32_t a, uint32_t b, uint32_t c) { uint32_t r; asm("prmt.b32 %0, %1, %2, %3;" : "=r"(r) : "r"(a), "r"(b), "r"(c)); return r; }
__device__ __forceinline__ uint4 lookup8_reg(const uint32_t* c, const uint32_t (&T)[8]) {
    uint32_t o[4];
#pragma unroll
    for (int h = 0; h < 2; h++) {
        const uint32_t sel = c[4 * h] + c[4 * h + 1] * 16 + c[4 * h + 2] * 256 + c[4 * h + 3] * 4096;
        const uint32_t s7 = sel & 0x7777u;
        uint32_t m;
        asm("lop3.b32 %0, %1, %2, 0x3210, 0xEA;" : "=r"(m) : "r"(sel >> 1), "r"(0x4444u));
        const uint32_t lo = prmt(prmt(T[0], T[1], s7), prmt(T[2], T[3], s7), m);
        const uint32_t hi = prmt(prmt(T[4], T[5], s7), prmt(T[6], T[7], s7), m);
        o[2 * h] = prmt(lo, hi, 0x5140u); o[2 * h + 1] = prmt(lo, hi, 0x7362u);
    }
    return make_uint4(o[0], o[1], o[2], o[3]);
}
template <int N>
__device__ __forceinline__ void pack_half(const float (&acc)[N], int H, uint32_t* r) {
    const int b = (H >> 1) * 16 + (H & 1) * 2;
#pragma unroll
    for (int i = 0; i < 4; i++) asm volatile("cvt.rn.bf16x2.f32 %0, %1, %2;" : "=r"(r[i]) : "f"(acc[b + 4 * i + 1]), "f"(acc[b + 4 * i]));
}
__device__ __forceinline__ void store_packed(__nv_bfloat16* o, int H, const uint32_t* r, int on = 1) {
    asm volatile("{\n.reg .pred p;\nsetp.ne.b32 p, %5, 0;\n@p st.global.v4.b32 [%0], {%1,%2,%3,%4};\n}"
                 ::"l"(o + (H & 1) * 8 * F_ + (H >> 1) * 32), "r"(r[0]), "r"(r[1]), "r"(r[2]), "r"(r[3]), "r"(on) : "memory");
}
template <int N>
__device__ __forceinline__ void store_half(const float (&acc)[N], __nv_bfloat16* o, int H, int on = 1) {
    const int b = (H >> 1) * 16 + (H & 1) * 2;
    const uint32_t r[4] = {pack_bf16(acc[b], acc[b + 1]), pack_bf16(acc[b + 4], acc[b + 5]), pack_bf16(acc[b + 8], acc[b + 9]), pack_bf16(acc[b + 12], acc[b + 13])};
    store_packed(o, H, r, on);
}
__device__ __forceinline__ unsigned clk() { unsigned c; asm volatile("mov.u32 %0, %%clock;" : "=r"(c)); return c; }
__device__ __forceinline__ void wait_until(unsigned t0, unsigned dt) { while (clk() - t0 < dt) {} }

#define TSK(w, i)
#define TS8(i)
#define TSW(w, i)
#define TS9(i)

template <bool HARD>
__global__ void __launch_bounds__(256, 1)
fused_kernel(const int* __restrict__ qw, const unsigned short* __restrict__ lut, __nv_bfloat16* __restrict__ out,
             uint4* __restrict__ wscr, unsigned* __restrict__ flags,
             const __grid_constant__ CUtensorMap tmq, const __grid_constant__ CUtensorMap tmx64, const __grid_constant__ CUtensorMap tmx
) {
    extern __shared__ uint8_t smem_raw[];
    const uint32_t sbase = HARD ? 1024u : (smem_u32(smem_raw) + 1023) & ~1023u;
    const uint32_t bars = sbase + OFF_BAR;
    const int tid = threadIdx.x, lane = tid & 31;
    const int mt = (blockIdx.x >> 6) * 4 + (blockIdx.x & 3), g = ((blockIdx.x >> 3) & 7) * 2 + ((blockIdx.x >> 2) & 1);
    const unsigned clk0 = clk();
    const int warp = __shfl_sync(0xffffffff, tid >> 5, 0);
    if (tid >= 224) {
        asm volatile("{\n.reg .pred p;\nelect.sync _|p, 0xffffffff;\n"
                     "@p mbarrier.init.shared::cta.b64 [%0], 1;\n"
                     "@p fence.mbarrier_init.release.cluster;\n"
                     "@p mbarrier.arrive.expect_tx.shared::cta.b64 _, [%0], %1;\n"
                     "@p cp.async.bulk.tensor.2d.shared::cluster.global.mbarrier::complete_tx::bytes [%3], [%2, {%4, 0}], [%0];\n}"
                     ::"r"(bars + 8 * B_SLAB), "n"(SLAB_BYTES), "l"(&tmq), "r"(sbase + OFF_SLAB0), "r"(g * BN) : "memory");
    } else {
        const unsigned short* lp = ptr_add(lut, ((lane >> 2) * F_ + g * BN + (tid & ~31) + (lane & 3) * 8) * 2);
        asm volatile("cp.async.cg.shared.global [%0], [%1], 16;\ncp.async.cg.shared.global [%0+512], [%1+57344], 16;\ncp.async.commit_group;"
                     ::"r"(sbase + OFF_STG + tid / 32 * 4096 + lane * 16), "l"(lp) : "memory");
    }
    const int sl = warp - 3;
    if (warp >= 4 && warp < 7) {
        asm volatile("{\n.reg .pred p;\nelect.sync _|p, 0xffffffff;\n"
                     "@p mbarrier.init.shared::cta.b64 [%0], 1;\n"
                     "@p fence.mbarrier_init.release.cluster;\n"
                     "@p mbarrier.arrive.expect_tx.shared::cta.b64 _, [%0], %1;\n}"
                     ::"r"(bars + 8 * (B_SLAB + sl)), "n"(SLAB_BYTES) : "memory");
    } else if (warp < 2) {
        asm volatile("{\n.reg .pred p;\nelect.sync _|p, 0xffffffff;\n"
                     "@p mbarrier.init.shared::cta.b64 [%0], %1;\n"
                     "@p fence.mbarrier_init.release.cluster;\n}" ::"r"(bars + 8 * (warp ? B_LUT : B_FULL)), "r"(warp ? 7 : 9) : "memory");
    }
    asm volatile("bar.sync 1, 256;" ::: "memory");
    const int wg = warp >> 2;

    const int fl = 8 * ((lane & 7) >> 1) + 2 * (lane >> 3) + (lane & 1);
    const uint32_t lut_a = sbase + OFF_LUT + warp * 2048 + lane * 4;
    const uint32_t stg = sbase + OFF_STG + warp * 4096;
    unsigned* myflags = flags + g * 32;
    const uint4* wgrp = wscr + (size_t)g * 128 * BN;
    unsigned target = 0;

    auto issue_x = [&](int s, int slot) {
        e_tma(bars + 8 * (B_FULL + s), &tmx, sbase + OFF_X + slot * X_BYTES, s * BK, mt * BM);
    };
    auto issue_xv = [&](int v, int bar) {
        e_expect(bars + 8 * bar, X_BYTES);
#pragma unroll
        for (int j = 0; j < 4; j++) e_tma(bars + 8 * bar, &tmx64, sbase + OFF_X + v * X_BYTES + j * 8192, (12 + 2 * v + (j & 1)) * BK, mt * BM + (j >> 1) * 128);
    };
    auto issue_w = [&](int s, int slot, int bar) {
        e_bulk(bars + 8 * bar, W_BYTES, sbase + OFF_W + slot * W_BYTES, wgrp + s * 8 * BN);
    };
    auto load_blk = [&](int t, int c) {
        const int* src = ptr_add(qw, (uint32_t)(((t * BK + mt * 8 + (lane >> 3)) * F_ + g * BN + c * 32 + (lane & 7) * 4) * 4));
        asm volatile("cp.async.cg.shared.global [%0], [%1], 16;\ncp.async.cg.shared.global [%0+512], [%1+57344], 16;"
                     ::"r"(sbase + OFF_STG + (t & 3) * 1024 + c * 4096 + lane * 16), "l"(src) : "memory");
    };
    auto load_raw = [&](int t) { if (t < 16) load_blk(t, warp); cp_commit(); };
    auto unit = [&](int t, int c) { return ptr_add(wscr, (uint32_t)(((g * 128 + t * 8 + mt) * BN + c * 32 + lane) * 16)); };
    auto foreign2 = [&]() {
        const int c = warp - 4;
        stg128(unit(2, c), dequant8(sbase + OFF_STG + 2 * 1024 + c * 4096 + fl * 4, sbase + OFF_LUT + c * 2048 + lane * 4));
    };
    auto coop = [&](int t) {
        cp_wait<1>();
        __syncwarp();
        load_raw(t + 2);
        stg128(unit(t, warp), dequant8(stg + (t & 3) * 1024 + fl * 4, lut_a));
    };

    if (warp == 7) {
        if (lane == 0) {
            asm volatile("prefetch.tensormap [%0];" ::"l"(&tmx) : "memory");
            asm volatile("prefetch.tensormap [%0];" ::"l"(&tmx64) : "memory");
        }
        __syncwarp();
        auto x0 = [&](int w, uint32_t bar) {
            e_expect(bar, X_BYTES / 2);
            e_tma(bar, &tmx64, sbase + OFF_X + w * 16384, 0, mt * BM + w * 128);
            e_tma(bar, &tmx64, sbase + OFF_X + w * 16384 + 8192, 0, mt * BM + w * 128 + 64);
        };
        auto inits = [&](int b0, int b1) {
            if (lane == 0) {
#pragma unroll
                for (int b = b0; b < b1; b++) mbar_init(bars + 8 * b, b < B_DQ + 4 ? 1 : 7);
#pragma unroll
                for (int b = b0; b < b1; b++)
                    if (b < B_XV || b == B_XV + 2 || b == B_XV + 3 || b == B_X15 || b == B_X15 + 1)
                        asm volatile("mbarrier.arrive.expect_tx.shared::cta.b64 _, [%0], %1;" ::"r"(bars + 8 * b), "r"(b < B_XV ? X_BYTES + W_BYTES : X_BYTES / 2) : "memory");
                asm volatile("fence.mbarrier_init.release.cluster;" ::: "memory");
            }
            __syncwarp();
        };
        inits(1, 9);
        wait_until(clk0, PX0);
        x0(0, bars + 8 * B_FULL);
        inits(9, B_SLAB - 1);
        e_arrive(bars + 8 * B_FULL);
        target = ld_flag(myflags + 6);
        wait_until(clk0, PR2);
        load_blk(2, 3);
        cp_commit();
        wait_until(clk0, PX0B);
        x0(1, bars + 8 * B_X0B);
        target = (target | 7) + 1;
        mbar_wait(bars + 8 * B_FULL);
        issue_x(1, 1);
        cp_wait<0>();
        __syncwarp();
        foreign2();
        TSW(7, 3);
    } else {
        if (wg == 1) e_tma(bars + 8 * (B_SLAB + sl), &tmq, sbase + (sl < 2 ? OFF_SLAB0 : OFF_SLAB2 - 2 * SLAB_BYTES) + sl * SLAB_BYTES, g * BN, sl * 16);
        wait_until(clk0, PR1);
        load_raw(1);
        uint32_t lv[16], v[32], T[8];
        cp_wait<1>();
        __syncwarp();
#pragma unroll
        for (int i = 0; i < 16; i++) asm volatile("ld.shared.u16 %0, [%1];" : "=r"(lv[i]) : "r"(stg + i * 64 + fl * 2));
#pragma unroll
        for (int i = 0; i < 16; i++) lv[i] = lv[i] ? lv[i] : 0x8000u;
#pragma unroll
        for (int i = 0; i < 4; i++) {
            const uint32_t p01 = prmt(lv[4 * i], lv[4 * i + 1], 0x5140u), p23 = prmt(lv[4 * i + 2], lv[4 * i + 3], 0x5140u);
            T[i] = prmt(p01, p23, 0x5410u); T[4 + i] = prmt(p01, p23, 0x7632u);
        }
        TSW(0, 7);
#pragma unroll
        for (int i = 0; i < 16; i++) sts32(lut_a + i * 128, lv[i]);
        __syncwarp();
        e_arrive(bars + 8 * B_LUT);
        auto own_task = [&](int t) {
            __syncwarp();
            uint32_t c[8];
#pragma unroll
            for (int i = 0; i < 8; i++) c[i] = lds32(stg + t * 1024 + fl * 4 + i * 128);
            stg128(unit(t, warp), lookup8_reg(c, T));
        };
        auto piece_ld = [&](int j) {
            mbar_wait(bars + 8 * (B_SLAB + j));
#pragma unroll
            for (int i = 0; i < 16; i++) v[(j & 1) * 16 + i] = lds32(sbase + (j < 2 ? OFF_SLAB0 : OFF_SLAB2) + (j & 1) * SLAB_BYTES + i * (BN * 4) + (warp * 32 + fl) * 4);
        };
        auto piece_st = [&](int j) {
            const uint32_t dst = sbase + OFF_W + j * 2 * CHUNK_BYTES + (warp * 32 + lane) * 16;
            sts128(dst, lookup8_reg(v + (j & 1) * 16, T));
            sts128(dst + CHUNK_BYTES, lookup8_reg(v + (j & 1) * 16 + 8, T));
            TSW(0, 8 + j);
        };
        piece_ld(0);
        piece_st(0);
        if (wg == 1) { load_blk(2, warp); load_blk(2, warp - 4); cp_commit(); }
        piece_ld(1);
        piece_ld(2);
        piece_st(1);
        piece_ld(3);
        piece_st(2);
        if (wg == 0) cp_wait<0>(); else cp_wait<1>();
        own_task(1);
        piece_st(3);
        asm volatile("fence.proxy.async.shared::cta;" ::: "memory");
        __syncwarp();
        e_arrive(bars + 8 * B_FULL);
        TSW(0, 14);
        if (wg == 1) {
            load_raw(3);
            cp_wait<1>();
            own_task(2);
            load_raw(4);
            mbar_wait(bars + 8 * B_LUT);
            foreign2();
        }
        TSW(4, 12);
    }

    float acc0[112], acc1[112];
    const uint64_t descA_hi = ((uint64_t)1 << 62) | ((uint64_t)(1024 >> 4) << 32) | ((uint64_t)1 << 16);
    const uint64_t descB_hi = ((uint64_t)(128 >> 4) << 32) | ((uint64_t)(CHUNK_BYTES >> 4) << 16);
    const uint32_t a16 = ((sbase & 0x3FFFF) >> 4) + wg * 1024 + (uint32_t)descA_hi, b16w = (((sbase + OFF_W) & 0x3FFFF) >> 4) + (uint32_t)descB_hi;
    auto dscA = [&](uint32_t lo) { return (descA_hi & 0xFFFFFFFF00000000ull) | lo; };
    auto dscB = [&](uint32_t lo) { return (descB_hi & 0xFFFFFFFF00000000ull) | lo; };
    uint32_t xo = 0, wo = 0, wo_prev = 2 * W_BYTES;
    const uint4* wnext = wgrp + 2 * 8 * BN;
    auto validate = [&](int t) {
        const uint32_t a = sbase + OFF_W + wo;
        for (int n = 0; n < 2000000; n++) {
            uint32_t m = 0xffffffffu;
#pragma unroll
            for (int i = 0; i < 7; i++) m = min(m, lds32(a + tid * 32 + (lane >> 2) * 4 + i * 4096));
            if (__all_sync(0xffffffff, m != 0)) break;
            const uint4* src = ptr_add(wgrp, (uint32_t)((t * 8 * BN + warp * 64 + lane) * 16));
#pragma unroll 1
            for (int i = 0; i < 14; i++) cp16(a + (warp * 64 + lane + (i >> 1) * 256 + (i & 1) * 32) * 16, src + (i >> 1) * 256 + (i & 1) * 32);
            cp_commit();
            cp_wait<0>();
            asm volatile("fence.proxy.async.shared::cta;" ::: "memory");
            __syncwarp();
        }
    };
    auto batch = [&](int s, bool in_loop) {
        mbar_wait(bars + 8 * (B_FULL + s));
        if (!in_loop && s == 0 && wg == 1) mbar_wait(bars + 8 * B_X0B);
        if (in_loop && wg == 0 && s <= NFAST) validate(s);
        if (s + wg > 0) asm volatile("bar.sync %0, 256;" ::"r"(2 + wg) : "memory");
        TSW(0, 16 + s); TSW(4, 48 + s); TS8(16 + s);
        const uint32_t al = a16 + (xo >> 4), bl = b16w + (wo >> 4);
        wgmma_fence();
#pragma unroll
        for (int kk = 0; kk < 4; kk++) {
            const uint64_t db = dscB(bl + kk * (2 * CHUNK_BYTES >> 4));
            wgmma_m64n224k16(acc0, dscA(al + kk * 2), db, in_loop || (s | kk) != 0);
            wgmma_m64n224k16(acc1, dscA(al + kk * 2 + (8192 >> 4)), db, in_loop || (s | kk) != 0);
        }
        wgmma_commit();
        asm volatile("bar.arrive %0, 256;" ::"r"(3 - wg) : "memory");
        TSW(0, 32 + s); TSW(4, 64 + s);
    };
    auto advance = [&]() {
        wo_prev = wo;
        xo = xo == 2 * X_BYTES ? 0 : xo + X_BYTES;
        wo = wo == 2 * W_BYTES ? 0 : wo + W_BYTES;
        wnext += 8 * BN;
    };
    batch(0, false);
#pragma unroll 1
    for (int s = 0; s < 9; s++) {
        const uint32_t bs = bars + 8 * s;
        if (warp == 7) {
            const int fb = (int)(W_FLAG >> (4 * s)) & 15, pb = (int)(R_BATCH >> (4 * s)) & 15;
            unsigned* fp = ptr_add(myflags, fb * 4);
            unsigned fv = target;
            const uint32_t l1 = (L1_MASK >> s) & 1, l2 = (L2_MASK >> s) & 1;
            if (s == 1) wait_until(clk(), W3D);
            if (fb) fv = ld_flag(fp);
            else e_bulk_p(l1, bs + 8 * (B_FULL + 2), W_BYTES, sbase + OFF_W + wo_prev, wnext);
            if (s == 0) {
                issue_x(2, 2);
                wait_until(clk(), W2D);
                e_bulk_p(1, bs + 8 * (B_FULL + 2), W_BYTES, sbase + OFF_W + wo_prev, wnext);
            }
            TSW(7, 112 + s);
            if (pb) {
                mbar_wait(bars + 8 * (B_DQ + pb));
                mbar_wait(bs + 8 * B_EMPTY);
                e_publish(ptr_add(myflags, pb * 4));
            } else {
                if (fb) {
                    finish_poll(fp, fv, target);
                    e_bulk_p(l1, bs + 8 * (B_FULL + 2), W_BYTES, sbase + OFF_W + wo_prev, wnext);
                }
                mbar_wait(bs + 8 * B_EMPTY);
                if (s == 8) {
                    issue_w(12, 3, B_WF);
                    e_bulk(bars + 8 * (B_WF + 3), W_BYTES / 2, sbase + OFF_LUT, wgrp + 15 * 8 * BN);
                }
            }
            wgmma_wait<0>();
            e_bulk_p(l2, bs + 8 * (B_FULL + 3), W_BYTES, sbase + OFF_W + wo, wnext + 8 * BN);
            e_tma(bs + 8 * (B_FULL + 3), &tmx, sbase + OFF_X + xo, (s + 3) * BK, mt * BM);
            TSW(7, 96 + s);
        } else {
            const int r = s + wg;
            if (r == 0) {
                if (warp == 3) {
                    wait_until(clk(), W1D);
                    e_bulk_p(1, bars + 8 * (B_FULL + 1), W_BYTES, sbase + OFF_W + W_BYTES, wgrp + 8 * BN);
                }
                load_raw(3); load_raw(4);
            } else if (r < 8) { coop(2 * r + 1); if (r < 7) coop(2 * r + 2); }
            const int b = (int)(R_BATCH >> (4 * r)) & 15;
            if (b) { __syncwarp(); e_arrive(bars + 8 * (B_DQ + b)); }
            TSW(0, 80 + s);
            wgmma_wait<0>();
            if (warp == 3) e_arrive(bs + 8 * B_EMPTY);
            if (warp == 2 && s == 8)
                asm volatile("{\n.reg .pred p;\nelect.sync _|p, 0xffffffff;\n@p cp.async.bulk.prefetch.tensor.2d.L2.global [%0, {%1, %2}];\n}"
                             ::"l"(&tmx64), "r"((12 + (g >> 2)) * BK), "r"(mt * BM + (g & 3) * 64) : "memory");
        }
        advance();
        batch(s + 1, true);
    }
    {
        if (warp == 7) mbar_wait(bars + 8 * (B_EMPTY + 9));
        wgmma_wait<0>();
        if (warp == 3) e_arrive(bars + 8 * (B_EMPTY + 9));
        if (warp == 7) {
            issue_w(13, 0, B_WF + 1);
            issue_xv(0, B_XV);
        }
        advance();
        batch(10, false);
        if (warp == 7) mbar_wait(bars + 8 * (B_EMPTY + 10));
        else {
            mbar_wait(bars + 8 * (B_FULL + 11));
#pragma unroll
            for (int t = 1; t <= NFAST; t++) stg128(unit(t, warp), make_uint4(0, 0, 0, 0));
        }
        wgmma_wait<0>();
        if (warp == 3) e_arrive(bars + 8 * (B_EMPTY + 10));
    }

    const int w4 = warp & 3;
    __nv_bfloat16* o = ptr_add(out, (uint32_t)(((mt * BM + wg * 128 + w4 * 16 + (lane >> 2)) * F_ + g * BN + (lane & 3) * 8) * 2));
    auto wofs = [](int st, int kk) -> uint32_t {
        return st < 15 ? OFF_W + (st == 11 ? 2 : st == 12 ? 3 : st - 13) * W_BYTES + kk * 2 * CHUNK_BYTES
                       : kk < 2 ? OFF_LUT + kk * 2 * CHUNK_BYTES : OFF_X + 2 * X_BYTES + (kk - 2) * 16384;
    };
    auto xofs = [](int st, int kk, int r) -> uint32_t {
        return (st == 11 ? 2 * X_BYTES + r * 8192 : ((st - 12) >> 1) * X_BYTES + (st & 1) * 8192) + kk * 32;
    };
    auto launder = [&]() { uint32_t b16 = (sbase & 0x3FFFF) >> 4; asm volatile("mov.u32 %0, %0;" : "+r"(b16)); return b16; };
    auto dA = [&](uint32_t b16, uint32_t ofs) { return dscA(b16 + wg * 1024 + (ofs >> 4) + (uint32_t)descA_hi); };
    auto dB = [&](uint32_t b16, uint32_t ofs) { return dscB(b16 + (ofs >> 4) + (uint32_t)descB_hi); };
    {
        mbar_wait(bars + 8 * (B_FULL + 11));
        asm volatile("bar.sync %0, 256;" ::"r"(2 + wg) : "memory");
        const uint32_t b16 = launder();
        wgmma_fence();
#pragma unroll
        for (int kk = 0; kk < 4; kk++) wgmma_m64n224k16(acc0, dA(b16, xofs(11, kk, 0)), dB(b16, wofs(11, kk)), 1);
        wgmma_commit();
        asm volatile("bar.arrive %0, 256;" ::"r"(3 - wg) : "memory");
        if (warp == 7) {
            issue_w(14, 1, B_WF + 2);
            issue_xv(1, B_XV + 1);
            mbar_wait(bars + 8 * (B_EMPTY + 11));
        }
        wgmma_wait<0>();
        if (warp == 3) e_arrive(bars + 8 * (B_EMPTY + 11));
        if (warp == 7) {
            e_bulk(bars + 8 * (B_WF + 4), 2 * CHUNK_BYTES, sbase + wofs(15, 2), wgrp + (15 * 8 + 4) * BN);
            e_bulk(bars + 8 * (B_XV + 4), 2 * CHUNK_BYTES, sbase + wofs(15, 3), wgrp + (15 * 8 + 6) * BN);
        }
    }
    {
        asm volatile("bar.sync %0, 256;" ::"r"(2 + wg) : "memory");
        TSK(0, 28);
        const uint32_t b16 = launder();
#pragma unroll
        for (int st = 12; st < 16; st++) {
            if (!(st & 1)) mbar_wait(bars + 8 * (B_XV + ((st - 12) >> 1)));
            mbar_wait(bars + 8 * (B_WF + st - 12));
            if (!(st & 1)) wgmma_fence();
#pragma unroll
            for (int kk = 0; kk < 4; kk++) {
                if (st == 15 && kk >= 2) mbar_wait(bars + 8 * (kk == 2 ? B_WF + 4 : B_XV + 4));
                wgmma_m64n224k16(acc0, dA(b16, xofs(st, kk, 0)), dB(b16, wofs(st, kk)), 1);
            }
            if (st & 1) wgmma_commit();
        }
        asm volatile("bar.arrive %0, 256;" ::"r"(3 - wg) : "memory");
    }
    float p0[64], p1[32], p2[16];
#pragma unroll
    for (int i = 0; i < 64; i++) asm volatile("add.f32 %0, %1, 0f00000000;" : "=f"(p0[i]) : "f"(acc1[i]));
#pragma unroll
    for (int i = 0; i < 32; i++) asm volatile("add.f32 %0, %1, 0f00000000;" : "=f"(p1[i]) : "f"(acc1[64 + i]));
#pragma unroll
    for (int i = 0; i < 16; i++) asm volatile("add.f32 %0, %1, 0f00000000;" : "=f"(p2[i]) : "f"(acc1[96 + i]));
    auto xlag = [&](int v, int bar) {
        if (w4 >= 2) e_tma(bars + 8 * (bar + wg), &tmx64, sbase + OFF_X + v * X_BYTES + wg * 16384 + (w4 - 2) * 8192, (10 + 2 * v + w4) * BK, mt * BM + wg * 128 + 64);
    };
    wgmma_wait<1>();
    xlag(0, B_XV + 2);
    wgmma_wait<0>();
    xlag(1, B_X15);
    TS9(0);
    uint32_t af[80], pk[(14 - CSP) * 4];
    const uint32_t lm = sbase + wg * 16384 + (w4 * 16 + (lane & 15)) * 128 + (((lane >> 4) ^ (lane & 7)) << 4);
    auto ldfrag = [&](int st) {
#pragma unroll
        for (int kk = 0; kk < 4; kk++) {
            uint32_t* r = af + ((st - 11) * 4 + kk) * 4;
            asm volatile("ldmatrix.sync.aligned.m8n8.x4.shared.b16 {%0,%1,%2,%3}, [%4];" : "=r"(r[0]), "=r"(r[1]), "=r"(r[2]), "=r"(r[3])
                         : "r"((lm ^ (kk << 5)) + xofs(st, 0, 1)) : "memory");
        }
    };
    unsigned tb = clk();
#pragma unroll
    for (int h = 0; h < CSP; h++) {
        if (h >= PSF) wait_until(tb, (h - PSF + 1) * PSTA);
        store_half(acc0, o, h);
        if (h == L11) ldfrag(11);
        if (h == L12) { mbar_wait(bars + 8 * (B_XV + 2 + wg)); ldfrag(12); }
    }
#pragma unroll
    for (int h = CSP; h < 14; h++) pack_half(acc0, h, pk + (h - CSP) * 4);
    asm volatile("bar.sync %0, 256;" ::"r"(2 + wg) : "memory");
    uint32_t b16 = launder();
#pragma unroll
    for (int st = 11; st < 16; st++) {
        wgmma_fence();
#pragma unroll
        for (int kk = 0; kk < 4; kk++) {
            const int i = (st - 11) * 4 + kk;
            wgmma_rs(p0, af + i * 4, dB(b16, wofs(st, kk)));
            if (i == 0) TS9(1);
            if (kk == 0 && st < 14) {
                if (st == 12) mbar_wait(bars + 8 * (B_X15 + wg));
                ldfrag(st + 2);
            }
            if (!(i & 1) && CSP + i / 2 < 14) store_packed(o, CSP + i / 2, pk + (i / 2) * 4);
        }
    }
    wgmma_commit();
    asm volatile("bar.arrive %0, 256;" ::"r"(3 - wg) : "memory");
    TS9(2);
    wgmma_wait<0>();
    TS9(3);
    tb = clk();
#pragma unroll
    for (int h = 0; h < DSP; h++) { wait_until(tb, wg ? h * PSTD : PSB0 + h * PSTB); store_half(p0, o + 64 * F_, h); }
    if (wg == 0) {
#pragma unroll
        for (int h = DSP; h < 8; h++) { wait_until(tb, PSB0 + h * PSTB); store_half(p0, o + 64 * F_, h); }
    }
    asm volatile("bar.sync %0, 256;" ::"r"(2 + wg) : "memory");
    b16 = launder();
    wgmma_fence();
#pragma unroll
    for (int i = 0; i < 20; i++) {
        wgmma_rs(p1, af + i * 4, dB(b16, wofs(11 + (i >> 2), i & 3) + 128 * 16));
        if (!(i & 1) && DSP + i / 2 < 8) store_half(p0, o + 64 * F_, DSP + i / 2, wg);
    }
    wgmma_commit();
    asm volatile("bar.arrive %0, 256;" ::"r"(3 - wg) : "memory");
    wgmma_wait<0>();
    TS9(4);
#pragma unroll
    for (int h = 0; h < 4; h++) store_half(p1, o + 64 * F_ + 128, h);
    asm volatile("bar.sync %0, 256;" ::"r"(2 + wg) : "memory");
    wgmma_fence();
#pragma unroll
    for (int i = 0; i < 20; i++) wgmma_rs(p2, af + i * 4, dB(b16, wofs(11 + (i >> 2), i & 3) + 192 * 16));
    wgmma_commit();
    if (wg == 0) asm volatile("bar.arrive 3, 256;" ::: "memory");
    wgmma_wait<0>();
    TSK(4, 63);
    store_half(p2, o + 64 * F_ + 192, 0);
    store_half(p2, o + 64 * F_ + 192, 1);
}

typedef CUresult (*EncodeTiledFn)(CUtensorMap*, CUtensorMapDataType, cuuint32_t, void*, const cuuint64_t*, const cuuint64_t*, const cuuint32_t*, const cuuint32_t*, CUtensorMapInterleave, CUtensorMapSwizzle, CUtensorMapL2promotion, CUtensorMapFloatOOBfill);

extern "C" void kernel_launch(void* const* d_in, const int* in_sizes, int n_in, void* d_out, int out_size) {
    static EncodeTiledFn enc = nullptr;
    static decltype(&fused_kernel<true>) kern = nullptr;
    static void *p_w = nullptr, *p_flags = nullptr, *p_prof = nullptr;
    if (!enc) {
        void* fn = nullptr; cudaDriverEntryPointQueryResult qr;
        cudaGetDriverEntryPoint("cuTensorMapEncodeTiled", &fn, cudaEnableDefault, &qr);
        enc = (EncodeTiledFn)fn;
        int dev = 0, rsv = 0;
        cudaGetDevice(&dev);
        cudaDeviceGetAttribute(&rsv, cudaDevAttrReservedSharedMemoryPerBlock, dev);
        kern = rsv == 1024 && !NOHARD ? fused_kernel<true> : fused_kernel<false>;
        cudaFuncSetAttribute(kern, cudaFuncAttributeMaxDynamicSharedMemorySize, SMEM_BYTES);
        cudaGetSymbolAddress(&p_w, g_w);
        cudaGetSymbolAddress(&p_flags, g_flags);
    }
    CUtensorMap tmx, tmx64, tmq;
    {
        cuuint64_t gdim[2] = {(cuuint64_t)F_, (cuuint64_t)D_};
        cuuint64_t gstr[1] = {(cuuint64_t)F_ * 4};
        cuuint32_t box[2] = {(cuuint32_t)BN, 16};
        cuuint32_t estr[2] = {1, 1};
        enc(&tmq, CU_TENSOR_MAP_DATA_TYPE_INT32, 2, d_in[1], gdim, gstr, box, estr, CU_TENSOR_MAP_INTERLEAVE_NONE,
            CU_TENSOR_MAP_SWIZZLE_NONE, CU_TENSOR_MAP_L2_PROMOTION_L2_128B, CU_TENSOR_MAP_FLOAT_OOB_FILL_NONE);
    }
    {
        cuuint64_t gdim[2] = {(cuuint64_t)D_, (cuuint64_t)S_};
        cuuint64_t gstr[1] = {(cuuint64_t)D_ * 2};
        cuuint32_t box[2] = {(cuuint32_t)BK, (cuuint32_t)BM};
        cuuint32_t estr[2] = {1, 1};
        enc(&tmx, CU_TENSOR_MAP_DATA_TYPE_BFLOAT16, 2, d_in[0], gdim, gstr, box, estr, CU_TENSOR_MAP_INTERLEAVE_NONE,
            CU_TENSOR_MAP_SWIZZLE_128B, CU_TENSOR_MAP_L2_PROMOTION_L2_128B, CU_TENSOR_MAP_FLOAT_OOB_FILL_NONE);
        box[1] = 64;
        enc(&tmx64, CU_TENSOR_MAP_DATA_TYPE_BFLOAT16, 2, d_in[0], gdim, gstr, box, estr, CU_TENSOR_MAP_INTERLEAVE_NONE,
            CU_TENSOR_MAP_SWIZZLE_128B, CU_TENSOR_MAP_L2_PROMOTION_L2_128B, CU_TENSOR_MAP_FLOAT_OOB_FILL_NONE);
    }
    kern<<<128, 256, SMEM_BYTES>>>((const int*)d_in[1], (const unsigned short*)d_in[2], (__nv_bfloat16*)d_out, (uint4*)p_w, (unsigned*)p_flags, tmq, tmx64, tmx
    );
    (void)p_prof;
}
```

```cpp
#include <cuda_runtime.h>
#include <cuda_bf16.h>
#include <cuda.h>
#include <stdint.h>
#include <stdio.h>

#define PR1 1150
#define PX0 950
#define PX0B 2600
#define PR2 2100
#define W1D 260
#define W2D 500
#define W3D 1000
#define CSP 10
#define PSTA 110
#define PSF 3
#define L11 4
#define L12 7
#define DSP 4
#define PSB0 150
#define PSTB 110
#define PSTD 100

#define NOHARD 0

constexpr int S_ = 2048, D_ = 1024, F_ = 3584;
constexpr int BM = 256, BN = 224, BK = 64;
constexpr int X_BYTES = BM * BK * 2;
constexpr int W_BYTES = BN * BK * 2;
constexpr int CHUNK_BYTES = BN * 16;
constexpr int SLAB_BYTES = 16 * BN * 4;
constexpr int OFF_X = 0;
constexpr int OFF_W = 3 * X_BYTES;
constexpr int OFF_STG = OFF_W + 3 * W_BYTES;
constexpr int OFF_LUT = OFF_W + 4 * W_BYTES;
constexpr int OFF_BAR = OFF_LUT + 7 * 2048;
constexpr int OFF_PROF = OFF_BAR + 1024;
constexpr int SMEM_BYTES = OFF_PROF + 1024 + 1024;
constexpr int OFF_SLAB0 = OFF_W + 2 * W_BYTES, OFF_SLAB2 = OFF_X + 2 * X_BYTES;
constexpr int B_FULL = 0;
constexpr int B_XV = 12;
constexpr int B_WF = 17;
constexpr int B_EMPTY = 22;
constexpr int B_X0B = 34;
constexpr int B_X15 = 35;
constexpr int B_DQ = 34;
constexpr int B_SLAB = 42;
constexpr int B_LUT = 46;
constexpr int NFAST = 4;
constexpr unsigned long long R_BATCH = 0x60050400ull, W_FLAG = 0x600504000ull;
constexpr unsigned L1_MASK = 0x2E, L2_MASK = 0x1E8;

__device__ __align__(1024) uint4 g_w[(size_t)F_ * D_ / 8];
__device__ __align__(128) unsigned g_flags[16 * 32];

__device__ __forceinline__ uint32_t smem_u32(const void* p) { return (uint32_t)__cvta_generic_to_shared(p); }
__device__ __forceinline__ void mbar_init(uint32_t bar, uint32_t cnt) { asm volatile("mbarrier.init.shared::cta.b64 [%0], %1;" ::"r"(bar), "r"(cnt) : "memory"); }
__device__ __forceinline__ void mbar_wait(uint32_t bar) {
    asm volatile("{\n.reg .pred p;\nWAIT_LOOP:\nmbarrier.try_wait.parity.shared::cta.b64 p, [%0], 0;\n@p bra WAIT_DONE;\nbra WAIT_LOOP;\nWAIT_DONE:\n}" ::"r"(bar) : "memory");
}
__device__ __forceinline__ void e_arrive(uint32_t bar) {
    asm volatile("{\n.reg .pred p;\nelect.sync _|p, 0xffffffff;\n@p mbarrier.arrive.shared::cta.b64 _, [%0];\n}" ::"r"(bar) : "memory");
}
__device__ __forceinline__ void e_expect(uint32_t bar, uint32_t bytes) {
    asm volatile("{\n.reg .pred p;\nelect.sync _|p, 0xffffffff;\n@p mbarrier.arrive.expect_tx.shared::cta.b64 _, [%0], %1;\n}" ::"r"(bar), "r"(bytes) : "memory");
}
__device__ __forceinline__ void e_tma(uint32_t bar, const CUtensorMap* tm, uint32_t d0, int x0, int y0) {
    asm volatile("{\n.reg .pred p;\nelect.sync _|p, 0xffffffff;\n"
                 "@p cp.async.bulk.tensor.2d.shared::cluster.global.mbarrier::complete_tx::bytes [%2], [%1, {%3, %4}], [%0];\n}"
                 ::"r"(bar), "l"(tm), "r"(d0), "r"(x0), "r"(y0) : "memory");
}
__device__ __forceinline__ void e_bulk(uint32_t bar, uint32_t bytes, uint32_t dst, const void* src) {
    asm volatile("{\n.reg .pred p;\nelect.sync _|p, 0xffffffff;\n"
                 "@p mbarrier.arrive.expect_tx.shared::cta.b64 _, [%0], %1;\n"
                 "@p cp.async.bulk.shared::cluster.global.mbarrier::complete_tx::bytes [%2], [%3], %1, [%0];\n}"
                 ::"r"(bar), "r"(bytes), "r"(dst), "l"(src) : "memory");
}
__device__ __forceinline__ void e_bulk_p(uint32_t on, uint32_t bar, uint32_t bytes, uint32_t dst, const void* src) {
    if (on) asm volatile("{\n.reg .pred p;\nelect.sync _|p, 0xffffffff;\n"
                         "@p cp.async.bulk.shared::cluster.global.mbarrier::complete_tx::bytes [%2], [%3], %1, [%0];\n}"
                         ::"r"(bar), "r"(bytes), "r"(dst), "l"(src) : "memory");
}
__device__ __forceinline__ void e_publish(unsigned* flag) {
    asm volatile("{\n.reg .pred p;\nelect.sync _|p, 0xffffffff;\n@p red.release.gpu.global.add.u32 [%0], 1;\n}" ::"l"(flag) : "memory");
}
__device__ __forceinline__ unsigned ld_flag(const unsigned* f) { unsigned v; asm volatile("ld.relaxed.gpu.global.u32 %0, [%1];" : "=r"(v) : "l"(f) : "memory"); return v; }
__device__ __forceinline__ void finish_poll(const unsigned* f, unsigned v, unsigned target) {
    int n = 0;
    while (!__all_sync(0xffffffff, (int)(v - target) >= 0) && ++n < 4000000) v = ld_flag(f);
    asm volatile("fence.acquire.gpu;" ::: "memory");
    asm volatile("fence.proxy.async.global;" ::: "memory");
}
template <typename T> __device__ __forceinline__ T* ptr_add(T* base, uint32_t off) {
    uint64_t r;
    asm("{\n.reg .u32 l, h;\nmov.b64 {l, h}, %1;\nadd.cc.u32 l, l, %2;\naddc.u32 h, h, 0;\nmov.b64 %0, {l, h};\n}" : "=l"(r) : "l"(base), "r"(off));
    return (T*)r;
}
__device__ __forceinline__ void wgmma_fence() { asm volatile("wgmma.fence.sync.aligned;" ::: "memory"); }
__device__ __forceinline__ void wgmma_commit() { asm volatile("wgmma.commit_group.sync.aligned;" ::: "memory"); }
template <int N> __device__ __forceinline__ void wgmma_wait() { asm volatile("wgmma.wait_group.sync.aligned %0;" ::"n"(N) : "memory"); }
__device__ __forceinline__ void wgmma_m64n224k16(float (&d)[112], uint64_t da, uint64_t db, int scale_d) {
    asm volatile(
        "{\n.reg .pred p;\nsetp.ne.b32 p, %114, 0;\n"
        "wgmma.mma_async.sync.aligned.m64n224k16.f32.bf16.bf16 "
        "{%0, %1, %2, %3, %4, %5, %6, %7, %8, %9, %10, %11, %12, %13, %14, %15, "
        "%16, %17, %18, %19, %20, %21, %22, %23, %24, %25, %26, %27, %28, %29, %30, %31, "
        "%32, %33, %34, %35, %36, %37, %38, %39, %40, %41, %42, %43, %44, %45, %46, %47, "
        "%48, %49, %50, %51, %52, %53, %54, %55, %56, %57, %58, %59, %60, %61, %62, %63, "
        "%64, %65, %66, %67, %68, %69, %70, %71, %72, %73, %74, %75, %76, %77, %78, %79, "
        "%80, %81, %82, %83, %84, %85, %86, %87, %88, %89, %90, %91, %92, %93, %94, %95, "
        "%96, %97, %98, %99, %100, %101, %102, %103, %104, %105, %106, %107, %108, %109, %110, %111}, "
        "%112, %113, p, 1, 1, 0, 0;\n}\n"
        : "+f"(d[0]), "+f"(d[1]), "+f"(d[2]), "+f"(d[3]), "+f"(d[4]), "+f"(d[5]), "+f"(d[6]), "+f"(d[7]),
          "+f"(d[8]), "+f"(d[9]), "+f"(d[10]), "+f"(d[11]), "+f"(d[12]), "+f"(d[13]), "+f"(d[14]), "+f"(d[15]),
          "+f"(d[16]), "+f"(d[17]), "+f"(d[18]), "+f"(d[19]), "+f"(d[20]), "+f"(d[21]), "+f"(d[22]), "+f"(d[23]),
          "+f"(d[24]), "+f"(d[25]), "+f"(d[26]), "+f"(d[27]), "+f"(d[28]), "+f"(d[29]), "+f"(d[30]), "+f"(d[31]),
          "+f"(d[32]), "+f"(d[33]), "+f"(d[34]), "+f"(d[35]), "+f"(d[36]), "+f"(d[37]), "+f"(d[38]), "+f"(d[39]),
          "+f"(d[40]), "+f"(d[41]), "+f"(d[42]), "+f"(d[43]), "+f"(d[44]), "+f"(d[45]), "+f"(d[46]), "+f"(d[47]),
          "+f"(d[48]), "+f"(d[49]), "+f"(d[50]), "+f"(d[51]), "+f"(d[52]), "+f"(d[53]), "+f"(d[54]), "+f"(d[55]),
          "+f"(d[56]), "+f"(d[57]), "+f"(d[58]), "+f"(d[59]), "+f"(d[60]), "+f"(d[61]), "+f"(d[62]), "+f"(d[63]),
          "+f"(d[64]), "+f"(d[65]), "+f"(d[66]), "+f"(d[67]), "+f"(d[68]), "+f"(d[69]), "+f"(d[70]), "+f"(d[71]),
          "+f"(d[72]), "+f"(d[73]), "+f"(d[74]), "+f"(d[75]), "+f"(d[76]), "+f"(d[77]), "+f"(d[78]), "+f"(d[79]),
          "+f"(d[80]), "+f"(d[81]), "+f"(d[82]), "+f"(d[83]), "+f"(d[84]), "+f"(d[85]), "+f"(d[86]), "+f"(d[87]),
          "+f"(d[88]), "+f"(d[89]), "+f"(d[90]), "+f"(d[91]), "+f"(d[92]), "+f"(d[93]), "+f"(d[94]), "+f"(d[95]),
          "+f"(d[96]), "+f"(d[97]), "+f"(d[98]), "+f"(d[99]), "+f"(d[100]), "+f"(d[101]), "+f"(d[102]), "+f"(d[103]),
          "+f"(d[104]), "+f"(d[105]), "+f"(d[106]), "+f"(d[107]), "+f"(d[108]), "+f"(d[109]), "+f"(d[110]), "+f"(d[111])
        : "l"(da), "l"(db), "r"(scale_d));
}

__device__ __forceinline__ void wgmma_rs(float (&d)[16], const uint32_t* a, uint64_t db) {
    asm volatile("wgmma.mma_async.sync.aligned.m64n32k16.f32.bf16.bf16 {%0, %1, %2, %3, %4, %5, %6, %7, %8, %9, %10, %11, %12, %13, %14, %15}, {%16, %17, %18, %19}, %20, 1, 1, 1, 0;"
        : "+f"(d[0]), "+f"(d[1]), "+f"(d[2]), "+f"(d[3]), "+f"(d[4]), "+f"(d[5]), "+f"(d[6]), "+f"(d[7]), "+f"(d[8]), "+f"(d[9]), "+f"(d[10]), "+f"(d[11]), "+f"(d[12]), "+f"(d[13]), "+f"(d[14]), "+f"(d[15])
        : "r"(a[0]), "r"(a[1]), "r"(a[2]), "r"(a[3]), "l"(db));
}
__device__ __forceinline__ void wgmma_rs(float (&d)[32], const uint32_t* a, uint64_t db) {
    asm volatile("wgmma.mma_async.sync.aligned.m64n64k16.f32.bf16.bf16 {%0, %1, %2, %3, %4, %5, %6, %7, %8, %9, %10, %11, %12, %13, %14, %15, %16, %17, %18, %19, %20, %21, %22, %23, %24, %25, %26, %27, %28, %29, %30, %31}, {%32, %33, %34, %35}, %36, 1, 1, 1, 0;"
        : "+f"(d[0]), "+f"(d[1]), "+f"(d[2]), "+f"(d[3]), "+f"(d[4]), "+f"(d[5]), "+f"(d[6]), "+f"(d[7]), "+f"(d[8]), "+f"(d[9]), "+f"(d[10]), "+f"(d[11]), "+f"(d[12]), "+f"(d[13]), "+f"(d[14]), "+f"(d[15]), "+f"(d[16]), "+f"(d[17]), "+f"(d[18]), "+f"(d[19]), "+f"(d[20]), "+f"(d[21]), "+f"(d[22]), "+f"(d[23]), "+f"(d[24]), "+f"(d[25]), "+f"(d[26]), "+f"(d[27]), "+f"(d[28]), "+f"(d[29]), "+f"(d[30]), "+f"(d[31])
        : "r"(a[0]), "r"(a[1]), "r"(a[2]), "r"(a[3]), "l"(db));
}
__device__ __forceinline__ void wgmma_rs(float (&d)[64], const uint32_t* a, uint64_t db) {
    asm volatile("wgmma.mma_async.sync.aligned.m64n128k16.f32.bf16.bf16 {%0, %1, %2, %3, %4, %5, %6, %7, %8, %9, %10, %11, %12, %13, %14, %15, %16, %17, %18, %19, %20, %21, %22, %23, %24, %25, %26, %27, %28, %29, %30, %31, %32, %33, %34, %35, %36, %37, %38, %39, %40, %41, %42, %43, %44, %45, %46, %47, %48, %49, %50, %51, %52, %53, %54, %55, %56, %57, %58, %59, %60, %61, %62, %63}, {%64, %65, %66, %67}, %68, 1, 1, 1, 0;"
        : "+f"(d[0]), "+f"(d[1]), "+f"(d[2]), "+f"(d[3]), "+f"(d[4]), "+f"(d[5]), "+f"(d[6]), "+f"(d[7]), "+f"(d[8]), "+f"(d[9]), "+f"(d[10]), "+f"(d[11]), "+f"(d[12]), "+f"(d[13]), "+f"(d[14]), "+f"(d[15]), "+f"(d[16]), "+f"(d[17]), "+f"(d[18]), "+f"(d[19]), "+f"(d[20]), "+f"(d[21]), "+f"(d[22]), "+f"(d[23]), "+f"(d[24]), "+f"(d[25]), "+f"(d[26]), "+f"(d[27]), "+f"(d[28]), "+f"(d[29]), "+f"(d[30]), "+f"(d[31]), "+f"(d[32]), "+f"(d[33]), "+f"(d[34]), "+f"(d[35]), "+f"(d[36]), "+f"(d[37]), "+f"(d[38]), "+f"(d[39]), "+f"(d[40]), "+f"(d[41]), "+f"(d[42]), "+f"(d[43]), "+f"(d[44]), "+f"(d[45]), "+f"(d[46]), "+f"(d[47]), "+f"(d[48]), "+f"(d[49]), "+f"(d[50]), "+f"(d[51]), "+f"(d[52]), "+f"(d[53]), "+f"(d[54]), "+f"(d[55]), "+f"(d[56]), "+f"(d[57]), "+f"(d[58]), "+f"(d[59]), "+f"(d[60]), "+f"(d[61]), "+f"(d[62]), "+f"(d[63])
        : "r"(a[0]), "r"(a[1]), "r"(a[2]), "r"(a[3]), "l"(db));
}

__device__ __forceinline__ uint32_t pack_bf16(float lo, float hi) {
    uint32_t r; asm("cvt.rn.bf16x2.f32 %0, %1, %2;" : "=r"(r) : "f"(hi), "f"(lo)); return r;
}
__device__ __forceinline__ uint32_t lds32(uint32_t a) { uint32_t v; asm volatile("ld.shared.b32 %0, [%1];" : "=r"(v) : "r"(a)); return v; }
__device__ __forceinline__ void sts32(uint32_t a, uint32_t v) { asm volatile("st.shared.b32 [%0], %1;" ::"r"(a), "r"(v) : "memory"); }
__device__ __forceinline__ void sts128(uint32_t a, uint4 v) { asm volatile("st.shared.v4.b32 [%0], {%1,%2,%3,%4};" ::"r"(a), "r"(v.x), "r"(v.y), "r"(v.z), "r"(v.w) : "memory"); }
__device__ __forceinline__ void stg128(void* p, uint4 v) { asm volatile("st.global.v4.b32 [%0], {%1,%2,%3,%4};" ::"l"(p), "r"(v.x), "r"(v.y), "r"(v.z), "r"(v.w) : "memory"); }
__device__ __forceinline__ void cp16(uint32_t dst, const void* src) { asm volatile("cp.async.cg.shared.global [%0], [%1], 16;" ::"r"(dst), "l"(src) : "memory"); }
__device__ __forceinline__ void cp_commit() { asm volatile("cp.async.commit_group;" ::: "memory"); }
template <int N> __device__ __forceinline__ void cp_wait() { asm volatile("cp.async.wait_group %0;" ::"n"(N) : "memory"); }
__device__ __forceinline__ uint4 dequant8(uint32_t raw, uint32_t lut_a) {
    uint32_t v[8];
#pragma unroll
    for (int i = 0; i < 8; i++) v[i] = lds32(raw + i * 128);
#pragma unroll
    for (int i = 0; i < 8; i++) v[i] = lds32(lut_a + v[i] * 128);
    uint4 o;
    o.x = __byte_perm(v[0], v[1], 0x5410); o.y = __byte_perm(v[2], v[3], 0x5410);
    o.z = __byte_perm(v[4], v[5], 0x5410); o.w = __byte_perm(v[6], v[7], 0x5410);
    return o;
}
__device__ __forceinline__ uint32_t prmt(uint32_t a, uint32_t b, uint32_t c) { uint32_t r; asm("prmt.b32 %0, %1, %2, %3;" : "=r"(r) : "r"(a), "r"(b), "r"(c)); return r; }
__device__ __forceinline__ uint4 lookup8_reg(const uint32_t* c, const uint32_t (&T)[8]) {
    uint32_t o[4];
#pragma unroll
    for (int h = 0; h < 2; h++) {
        const uint32_t sel = c[4 * h] + c[4 * h + 1] * 16 + c[4 * h + 2] * 256 + c[4 * h + 3] * 4096;
        const uint32_t s7 = sel & 0x7777u;
        uint32_t m;
        asm("lop3.b32 %0, %1, %2, 0x3210, 0xEA;" : "=r"(m) : "r"(sel >> 1), "r"(0x4444u));
        const uint32_t lo = prmt(prmt(T[0], T[1], s7), prmt(T[2], T[3], s7), m);
        const uint32_t hi = prmt(prmt(T[4], T[5], s7), prmt(T[6], T[7], s7), m);
        o[2 * h] = prmt(lo, hi, 0x5140u); o[2 * h + 1] = prmt(lo, hi, 0x7362u);
    }
    return make_uint4(o[0], o[1], o[2], o[3]);
}
template <int N>
__device__ __forceinline__ void pack_half(const float (&acc)[N], int H, uint32_t* r) {
    const int b = (H >> 1) * 16 + (H & 1) * 2;
#pragma unroll
    for (int i = 0; i < 4; i++) asm volatile("cvt.rn.bf16x2.f32 %0, %1, %2;" : "=r"(r[i]) : "f"(acc[b + 4 * i + 1]), "f"(acc[b + 4 * i]));
}
__device__ __forceinline__ void store_packed(__nv_bfloat16* o, int H, const uint32_t* r, int on = 1) {
    asm volatile("{\n.reg .pred p;\nsetp.ne.b32 p, %5, 0;\n@p st.global.v4.b32 [%0], {%1,%2,%3,%4};\n}"
                 ::"l"(o + (H & 1) * 8 * F_ + (H >> 1) * 32), "r"(r[0]), "r"(r[1]), "r"(r[2]), "r"(r[3]), "r"(on) : "memory");
}
template <int N>
__device__ __forceinline__ void store_half(const float (&acc)[N], __nv_bfloat16* o, int H, int on = 1) {
    const int b = (H >> 1) * 16 + (H & 1) * 2;
    const uint32_t r[4] = {pack_bf16(acc[b], acc[b + 1]), pack_bf16(acc[b + 4], acc[b + 5]), pack_bf16(acc[b + 8], acc[b + 9]), pack_bf16(acc[b + 12], acc[b + 13])};
    store_packed(o, H, r, on);
}
__device__ __forceinline__ unsigned clk() { unsigned c; asm volatile("mov.u32 %0, %%clock;" : "=r"(c)); return c; }
__device__ __forceinline__ void wait_until(unsigned t0, unsigned dt) { while (clk() - t0 < dt) {} }

template <bool HARD>
__global__ void __launch_bounds__(256, 1)
fused_kernel(const int* __restrict__ qw, const unsigned short* __restrict__ lut, __nv_bfloat16* __restrict__ out,
             uint4* __restrict__ wscr, unsigned* __restrict__ flags,
             const __grid_constant__ CUtensorMap tmq, const __grid_constant__ CUtensorMap tmx64, const __grid_constant__ CUtensorMap tmx
) {
    extern __shared__ uint8_t smem_raw[];
    const uint32_t sbase = HARD ? 1024u : (smem_u32(smem_raw) + 1023) & ~1023u;
    const uint32_t bars = sbase + OFF_BAR;
    const int tid = threadIdx.x, lane = tid & 31;
    const int mt = (blockIdx.x >> 6) * 4 + (blockIdx.x & 3), g = ((blockIdx.x >> 3) & 7) * 2 + ((blockIdx.x >> 2) & 1);
    const unsigned clk0 = clk();
    const int warp = __shfl_sync(0xffffffff, tid >> 5, 0);
    if (tid >= 224) {
        asm volatile("{\n.reg .pred p;\nelect.sync _|p, 0xffffffff;\n"
                     "@p mbarrier.init.shared::cta.b64 [%0], 1;\n"
                     "@p fence.mbarrier_init.release.cluster;\n"
                     "@p mbarrier.arrive.expect_tx.shared::cta.b64 _, [%0], %1;\n"
                     "@p cp.async.bulk.tensor.2d.shared::cluster.global.mbarrier::complete_tx::bytes [%3], [%2, {%4, 0}], [%0];\n}"
                     ::"r"(bars + 8 * B_SLAB), "n"(SLAB_BYTES), "l"(&tmq), "r"(sbase + OFF_SLAB0), "r"(g * BN) : "memory");
    } else {
        const unsigned short* lp = ptr_add(lut, ((lane >> 2) * F_ + g * BN + (tid & ~31) + (lane & 3) * 8) * 2);
        asm volatile("cp.async.cg.shared.global [%0], [%1], 16;\ncp.async.cg.shared.global [%0+512], [%1+57344], 16;\ncp.async.commit_group;"
                     ::"r"(sbase + OFF_STG + tid / 32 * 4096 + lane * 16), "l"(lp) : "memory");
    }
    const int sl = warp - 3;
    if (warp >= 4 && warp < 7) {
        asm volatile("{\n.reg .pred p;\nelect.sync _|p, 0xffffffff;\n"
                     "@p mbarrier.init.shared::cta.b64 [%0], 1;\n"
                     "@p fence.mbarrier_init.release.cluster;\n"
                     "@p mbarrier.arrive.expect_tx.shared::cta.b64 _, [%0], %1;\n}"
                     ::"r"(bars + 8 * (B_SLAB + sl)), "n"(SLAB_BYTES) : "memory");
    } else if (warp < 2) {
        asm volatile("{\n.reg .pred p;\nelect.sync _|p, 0xffffffff;\n"
                     "@p mbarrier.init.shared::cta.b64 [%0], %1;\n"
                     "@p fence.mbarrier_init.release.cluster;\n}" ::"r"(bars + 8 * (warp ? B_LUT : B_FULL)), "r"(warp ? 7 : 9) : "memory");
    }
    asm volatile("bar.sync 1, 256;" ::: "memory");
    const int wg = warp >> 2;

    const int fl = 8 * ((lane & 7) >> 1) + 2 * (lane >> 3) + (lane & 1);
    const uint32_t lut_a = sbase + OFF_LUT + warp * 2048 + lane * 4;
    const uint32_t stg = sbase + OFF_STG + warp * 4096;
    unsigned* myflags = flags + g * 32;
    const uint4* wgrp = wscr + (size_t)g * 128 * BN;
    unsigned target = 0;

    auto issue_x = [&](int s, int slot) {
        e_tma(bars + 8 * (B_FULL + s), &tmx, sbase + OFF_X + slot * X_BYTES, s * BK, mt * BM);
    };
    auto issue_xv = [&](int v, int bar) {
        e_expect(bars + 8 * bar, X_BYTES);
#pragma unroll
        for (int j = 0; j < 4; j++) e_tma(bars + 8 * bar, &tmx64, sbase + OFF_X + v * X_BYTES + j * 8192, (12 + 2 * v + (j & 1)) * BK, mt * BM + (j >> 1) * 128);
    };
    auto issue_w = [&](int s, int slot, int bar) {
        e_bulk(bars + 8 * bar, W_BYTES, sbase + OFF_W + slot * W_BYTES, wgrp + s * 8 * BN);
    };
    auto load_blk = [&](int t, int c) {
        const int* src = ptr_add(qw, (uint32_t)(((t * BK + mt * 8 + (lane >> 3)) * F_ + g * BN + c * 32 + (lane & 7) * 4) * 4));
        asm volatile("cp.async.cg.shared.global [%0], [%1], 16;\ncp.async.cg.shared.global [%0+512], [%1+57344], 16;"
                     ::"r"(sbase + OFF_STG + (t & 3) * 1024 + c * 4096 + lane * 16), "l"(src) : "memory");
    };
    auto load_raw = [&](int t) { if (t < 16) load_blk(t, warp); cp_commit(); };
    auto unit = [&](int t, int c) { return ptr_add(wscr, (uint32_t)(((g * 128 + t * 8 + mt) * BN + c * 32 + lane) * 16)); };
    auto foreign2 = [&]() {
        const int c = warp - 4;
        stg128(unit(2, c), dequant8(sbase + OFF_STG + 2 * 1024 + c * 4096 + fl * 4, sbase + OFF_LUT + c * 2048 + lane * 4));
    };
    auto coop = [&](int t) {
        cp_wait<1>();
        __syncwarp();
        load_raw(t + 2);
        stg128(unit(t, warp), dequant8(stg + (t & 3) * 1024 + fl * 4, lut_a));
    };

    if (warp == 7) {
        if (lane == 0) {
            asm volatile("prefetch.tensormap [%0];" ::"l"(&tmx) : "memory");
            asm volatile("prefetch.tensormap [%0];" ::"l"(&tmx64) : "memory");
        }
        __syncwarp();
        auto x0 = [&](int w, uint32_t bar) {
            e_expect(bar, X_BYTES / 2);
            e_tma(bar, &tmx64, sbase + OFF_X + w * 16384, 0, mt * BM + w * 128);
            e_tma(bar, &tmx64, sbase + OFF_X + w * 16384 + 8192, 0, mt * BM + w * 128 + 64);
        };
        auto inits = [&](int b0, int b1) {
            if (lane == 0) {
#pragma unroll
                for (int b = b0; b < b1; b++) mbar_init(bars + 8 * b, b < B_DQ + 4 ? 1 : 7);
#pragma unroll
                for (int b = b0; b < b1; b++)
                    if (b < B_XV || b == B_XV + 2 || b == B_XV + 3 || b == B_X15 || b == B_X15 + 1)
                        asm volatile("mbarrier.arrive.expect_tx.shared::cta.b64 _, [%0], %1;" ::"r"(bars + 8 * b), "r"(b < B_XV ? X_BYTES + W_BYTES : X_BYTES / 2) : "memory");
                asm volatile("fence.mbarrier_init.release.cluster;" ::: "memory");
            }
            __syncwarp();
        };
        inits(1, 9);
        wait_until(clk0, PX0);
        x0(0, bars + 8 * B_FULL);
        inits(9, B_SLAB - 1);
        e_arrive(bars + 8 * B_FULL);
        target = ld_flag(myflags + 6);
        wait_until(clk0, PR2);
        load_blk(2, 3);
        cp_commit();
        wait_until(clk0, PX0B);
        x0(1, bars + 8 * B_X0B);
        target = (target | 7) + 1;
        mbar_wait(bars + 8 * B_FULL);
        issue_x(1, 1);
        cp_wait<0>();
        __syncwarp();
        foreign2();
    } else {
        if (wg == 1) e_tma(bars + 8 * (B_SLAB + sl), &tmq, sbase + (sl < 2 ? OFF_SLAB0 : OFF_SLAB2 - 2 * SLAB_BYTES) + sl * SLAB_BYTES, g * BN, sl * 16);
        wait_until(clk0, PR1);
        load_raw(1);
        uint32_t lv[16], v[32], T[8];
        cp_wait<1>();
        __syncwarp();
#pragma unroll
        for (int i = 0; i < 16; i++) asm volatile("ld.shared.u16 %0, [%1];" : "=r"(lv[i]) : "r"(stg + i * 64 + fl * 2));
#pragma unroll
        for (int i = 0; i < 16; i++) lv[i] = lv[i] ? lv[i] : 0x8000u;
#pragma unroll
        for (int i = 0; i < 4; i++) {
            const uint32_t p01 = prmt(lv[4 * i], lv[4 * i + 1], 0x5140u), p23 = prmt(lv[4 * i + 2], lv[4 * i + 3], 0x5140u);
            T[i] = prmt(p01, p23, 0x5410u); T[4 + i] = prmt(p01, p23, 0x7632u);
        }
#pragma unroll
        for (int i = 0; i < 16; i++) sts32(lut_a + i * 128, lv[i]);
        __syncwarp();
        e_arrive(bars + 8 * B_LUT);
        auto own_task = [&](int t) {
            __syncwarp();
            uint32_t c[8];
#pragma unroll
            for (int i = 0; i < 8; i++) c[i] = lds32(stg + t * 1024 + fl * 4 + i * 128);
            stg128(unit(t, warp), lookup8_reg(c, T));
        };
        auto piece_ld = [&](int j) {
            mbar_wait(bars + 8 * (B_SLAB + j));
#pragma unroll
            for (int i = 0; i < 16; i++) v[(j & 1) * 16 + i] = lds32(sbase + (j < 2 ? OFF_SLAB0 : OFF_SLAB2) + (j & 1) * SLAB_BYTES + i * (BN * 4) + (warp * 32 + fl) * 4);
        };
        auto piece_st = [&](int j) {
            const uint32_t dst = sbase + OFF_W + j * 2 * CHUNK_BYTES + (warp * 32 + lane) * 16;
            sts128(dst, lookup8_reg(v + (j & 1) * 16, T));
            sts128(dst + CHUNK_BYTES, lookup8_reg(v + (j & 1) * 16 + 8, T));
        };
        piece_ld(0);
        piece_st(0);
        if (wg == 1) { load_blk(2, warp); load_blk(2, warp - 4); cp_commit(); }
        piece_ld(1);
        piece_ld(2);
        piece_st(1);
        piece_ld(3);
        piece_st(2);
        if (wg == 0) cp_wait<0>(); else cp_wait<1>();
        own_task(1);
        piece_st(3);
        asm volatile("fence.proxy.async.shared::cta;" ::: "memory");
        __syncwarp();
        e_arrive(bars + 8 * B_FULL);
        if (wg == 1) {
            load_raw(3);
            cp_wait<1>();
            own_task(2);
            load_raw(4);
            mbar_wait(bars + 8 * B_LUT);
            foreign2();
        }
    }

    float acc0[112], acc1[112];
    const uint64_t descA_hi = ((uint64_t)1 << 62) | ((uint64_t)(1024 >> 4) << 32) | ((uint64_t)1 << 16);
    const uint64_t descB_hi = ((uint64_t)(128 >> 4) << 32) | ((uint64_t)(CHUNK_BYTES >> 4) << 16);
    const uint32_t a16 = ((sbase & 0x3FFFF) >> 4) + wg * 1024 + (uint32_t)descA_hi, b16w = (((sbase + OFF_W) & 0x3FFFF) >> 4) + (uint32_t)descB_hi;
    auto dscA = [&](uint32_t lo) { return (descA_hi & 0xFFFFFFFF00000000ull) | lo; };
    auto dscB = [&](uint32_t lo) { return (descB_hi & 0xFFFFFFFF00000000ull) | lo; };
    uint32_t xo = 0, wo = 0, wo_prev = 2 * W_BYTES;
    const uint4* wnext = wgrp + 2 * 8 * BN;
    auto validate = [&](int t) {
        const uint32_t a = sbase + OFF_W + wo;
        for (int n = 0; n < 2000000; n++) {
            uint32_t m = 0xffffffffu;
#pragma unroll
            for (int i = 0; i < 7; i++) m = min(m, lds32(a + tid * 32 + (lane >> 2) * 4 + i * 4096));
            if (__all_sync(0xffffffff, m != 0)) break;
            const uint4* src = ptr_add(wgrp, (uint32_t)((t * 8 * BN + warp * 64 + lane) * 16));
#pragma unroll 1
            for (int i = 0; i < 14; i++) cp16(a + (warp * 64 + lane + (i >> 1) * 256 + (i & 1) * 32) * 16, src + (i >> 1) * 256 + (i & 1) * 32);
            cp_commit();
            cp_wait<0>();
            asm volatile("fence.proxy.async.shared::cta;" ::: "memory");
            __syncwarp();
        }
    };
    auto batch = [&](int s, bool in_loop) {
        mbar_wait(bars + 8 * (B_FULL + s));
        if (!in_loop && s == 0 && wg == 1) mbar_wait(bars + 8 * B_X0B);
        if (in_loop && wg == 0 && s <= NFAST) validate(s);
        if (s + wg > 0) asm volatile("bar.sync %0, 256;" ::"r"(2 + wg) : "memory");
        const uint32_t al = a16 + (xo >> 4), bl = b16w + (wo >> 4);
        wgmma_fence();
#pragma unroll
        for (int kk = 0; kk < 4; kk++) {
            const uint64_t db = dscB(bl + kk * (2 * CHUNK_BYTES >> 4));
            wgmma_m64n224k16(acc0, dscA(al + kk * 2), db, in_loop || (s | kk) != 0);
            wgmma_m64n224k16(acc1, dscA(al + kk * 2 + (8192 >> 4)), db, in_loop || (s | kk) != 0);
        }
        wgmma_commit();
        asm volatile("bar.arrive %0, 256;" ::"r"(3 - wg) : "memory");
    };
    auto advance = [&]() {
        wo_prev = wo;
        xo = xo == 2 * X_BYTES ? 0 : xo + X_BYTES;
        wo = wo == 2 * W_BYTES ? 0 : wo + W_BYTES;
        wnext += 8 * BN;
    };
    batch(0, false);
#pragma unroll 1
    for (int s = 0; s < 9; s++) {
        const uint32_t bs = bars + 8 * s;
        if (warp == 7) {
            const int fb = (int)(W_FLAG >> (4 * s)) & 15, pb = (int)(R_BATCH >> (4 * s)) & 15;
            unsigned* fp = ptr_add(myflags, fb * 4);
            unsigned fv = target;
            const uint32_t l1 = (L1_MASK >> s) & 1, l2 = (L2_MASK >> s) & 1;
            if (s == 1) wait_until(clk(), W3D);
            if (fb) fv = ld_flag(fp);
            else e_bulk_p(l1, bs + 8 * (B_FULL + 2), W_BYTES, sbase + OFF_W + wo_prev, wnext);
            if (s == 0) {
                issue_x(2, 2);
                wait_until(clk(), W2D);
                e_bulk_p(1, bs + 8 * (B_FULL + 2), W_BYTES, sbase + OFF_W + wo_prev, wnext);
            }
            if (pb) {
                mbar_wait(bars + 8 * (B_DQ + pb));
                mbar_wait(bs + 8 * B_EMPTY);
                e_publish(ptr_add(myflags, pb * 4));
            } else {
                if (fb) {
                    finish_poll(fp, fv, target);
                    e_bulk_p(l1, bs + 8 * (B_FULL + 2), W_BYTES, sbase + OFF_W + wo_prev, wnext);
                }
                mbar_wait(bs + 8 * B_EMPTY);
                if (s == 8) {
                    issue_w(12, 3, B_WF);
                    e_bulk(bars + 8 * (B_WF + 3), W_BYTES / 2, sbase + OFF_LUT, wgrp + 15 * 8 * BN);
                }
            }
            wgmma_wait<0>();
            e_bulk_p(l2, bs + 8 * (B_FULL + 3), W_BYTES, sbase + OFF_W + wo, wnext + 8 * BN);
            e_tma(bs + 8 * (B_FULL + 3), &tmx, sbase + OFF_X + xo, (s + 3) * BK, mt * BM);
        } else {
            const int r = s + wg;
            if (r == 0) {
                if (warp == 3) {
                    wait_until(clk(), W1D);
                    e_bulk_p(1, bars + 8 * (B_FULL + 1), W_BYTES, sbase + OFF_W + W_BYTES, wgrp + 8 * BN);
                }
                load_raw(3); load_raw(4);
            } else if (r < 8) { coop(2 * r + 1); if (r < 7) coop(2 * r + 2); }
            const int b = (int)(R_BATCH >> (4 * r)) & 15;
            if (b) { __syncwarp(); e_arrive(bars + 8 * (B_DQ + b)); }
            wgmma_wait<0>();
            if (warp == 3) e_arrive(bs + 8 * B_EMPTY);
            if (warp == 2 && s == 8)
                asm volatile("{\n.reg .pred p;\nelect.sync _|p, 0xffffffff;\n@p cp.async.bulk.prefetch.tensor.2d.L2.global [%0, {%1, %2}];\n}"
                             ::"l"(&tmx64), "r"((12 + (g >> 2)) * BK), "r"(mt * BM + (g & 3) * 64) : "memory");
        }
        advance();
        batch(s + 1, true);
    }
    {
        if (warp == 7) mbar_wait(bars + 8 * (B_EMPTY + 9));
        wgmma_wait<0>();
        if (warp == 3) e_arrive(bars + 8 * (B_EMPTY + 9));
        if (warp == 7) {
            issue_w(13, 0, B_WF + 1);
            issue_xv(0, B_XV);
        }
        advance();
        batch(10, false);
        if (warp == 7) mbar_wait(bars + 8 * (B_EMPTY + 10));
        else {
            mbar_wait(bars + 8 * (B_FULL + 11));
#pragma unroll
            for (int t = 1; t <= NFAST; t++) stg128(unit(t, warp), make_uint4(0, 0, 0, 0));
        }
        wgmma_wait<0>();
        if (warp == 3) e_arrive(bars + 8 * (B_EMPTY + 10));
    }

    const int w4 = warp & 3;
    __nv_bfloat16* o = ptr_add(out, (uint32_t)(((mt * BM + wg * 128 + w4 * 16 + (lane >> 2)) * F_ + g * BN + (lane & 3) * 8) * 2));
    auto wofs = [](int st, int kk) -> uint32_t {
        return st < 15 ? OFF_W + (st == 11 ? 2 : st == 12 ? 3 : st - 13) * W_BYTES + kk * 2 * CHUNK_BYTES
                       : kk < 2 ? OFF_LUT + kk * 2 * CHUNK_BYTES : OFF_X + 2 * X_BYTES + (kk - 2) * 16384;
    };
    auto xofs = [](int st, int kk, int r) -> uint32_t {
        return (st == 11 ? 2 * X_BYTES + r * 8192 : ((st - 12) >> 1) * X_BYTES + (st & 1) * 8192) + kk * 32;
    };
    auto launder = [&]() { uint32_t b16 = (sbase & 0x3FFFF) >> 4; asm volatile("mov.u32 %0, %0;" : "+r"(b16)); return b16; };
    auto dA = [&](uint32_t b16, uint32_t ofs) { return dscA(b16 + wg * 1024 + (ofs >> 4) + (uint32_t)descA_hi); };
    auto dB = [&](uint32_t b16, uint32_t ofs) { return dscB(b16 + (ofs >> 4) + (uint32_t)descB_hi); };
    {
        mbar_wait(bars + 8 * (B_FULL + 11));
        asm volatile("bar.sync %0, 256;" ::"r"(2 + wg) : "memory");
        const uint32_t b16 = launder();
        wgmma_fence();
#pragma unroll
        for (int kk = 0; kk < 4; kk++) wgmma_m64n224k16(acc0, dA(b16, xofs(11, kk, 0)), dB(b16, wofs(11, kk)), 1);
        wgmma_commit();
        asm volatile("bar.arrive %0, 256;" ::"r"(3 - wg) : "memory");
        if (warp == 7) {
            issue_w(14, 1, B_WF + 2);
            issue_xv(1, B_XV + 1);
            mbar_wait(bars + 8 * (B_EMPTY + 11));
        }
        wgmma_wait<0>();
        if (warp == 3) e_arrive(bars + 8 * (B_EMPTY + 11));
        if (warp == 7) {
            e_bulk(bars + 8 * (B_WF + 4), 2 * CHUNK_BYTES, sbase + wofs(15, 2), wgrp + (15 * 8 + 4) * BN);
            e_bulk(bars + 8 * (B_XV + 4), 2 * CHUNK_BYTES, sbase + wofs(15, 3), wgrp + (15 * 8 + 6) * BN);
        }
    }
    {
        asm volatile("bar.sync %0, 256;" ::"r"(2 + wg) : "memory");
        const uint32_t b16 = launder();
#pragma unroll
        for (int st = 12; st < 16; st++) {
            if (!(st & 1)) mbar_wait(bars + 8 * (B_XV + ((st - 12) >> 1)));
            mbar_wait(bars + 8 * (B_WF + st - 12));
            if (!(st & 1)) wgmma_fence();
#pragma unroll
            for (int kk = 0; kk < 4; kk++) {
                if (st == 15 && kk >= 2) mbar_wait(bars + 8 * (kk == 2 ? B_WF + 4 : B_XV + 4));
                wgmma_m64n224k16(acc0, dA(b16, xofs(st, kk, 0)), dB(b16, wofs(st, kk)), 1);
            }
            if (st & 1) wgmma_commit();
        }
        asm volatile("bar.arrive %0, 256;" ::"r"(3 - wg) : "memory");
    }
    float p0[64], p1[32], p2[16];
#pragma unroll
    for (int i = 0; i < 64; i++) asm volatile("add.f32 %0, %1, 0f00000000;" : "=f"(p0[i]) : "f"(acc1[i]));
#pragma unroll
    for (int i = 0; i < 32; i++) asm volatile("add.f32 %0, %1, 0f00000000;" : "=f"(p1[i]) : "f"(acc1[64 + i]));
#pragma unroll
    for (int i = 0; i < 16; i++) asm volatile("add.f32 %0, %1, 0f00000000;" : "=f"(p2[i]) : "f"(acc1[96 + i]));
    auto xlag = [&](int v, int bar) {
        if (w4 >= 2) e_tma(bars + 8 * (bar + wg), &tmx64, sbase + OFF_X + v * X_BYTES + wg * 16384 + (w4 - 2) * 8192, (10 + 2 * v + w4) * BK, mt * BM + wg * 128 + 64);
    };
    wgmma_wait<1>();
    xlag(0, B_XV + 2);
    wgmma_wait<0>();
    xlag(1, B_X15);
    uint32_t af[80], pk[(14 - CSP) * 4];
    const uint32_t lm = sbase + wg * 16384 + (w4 * 16 + (lane & 15)) * 128 + (((lane >> 4) ^ (lane & 7)) << 4);
    auto ldfrag = [&](int st) {
#pragma unroll
        for (int kk = 0; kk < 4; kk++) {
            uint32_t* r = af + ((st - 11) * 4 + kk) * 4;
            asm volatile("ldmatrix.sync.aligned.m8n8.x4.shared.b16 {%0,%1,%2,%3}, [%4];" : "=r"(r[0]), "=r"(r[1]), "=r"(r[2]), "=r"(r[3])
                         : "r"((lm ^ (kk << 5)) + xofs(st, 0, 1)) : "memory");
        }
    };
    unsigned tb = clk();
#pragma unroll
    for (int h = 0; h < CSP; h++) {
        if (h >= PSF) wait_until(tb, (h - PSF + 1) * PSTA);
        store_half(acc0, o, h);
        if (h == L11) ldfrag(11);
        if (h == L12) { mbar_wait(bars + 8 * (B_XV + 2 + wg)); ldfrag(12); }
    }
#pragma unroll
    for (int h = CSP; h < 14; h++) pack_half(acc0, h, pk + (h - CSP) * 4);
    asm volatile("bar.sync %0, 256;" ::"r"(2 + wg) : "memory");
    uint32_t b16 = launder();
#pragma unroll
    for (int st = 11; st < 16; st++) {
        wgmma_fence();
#pragma unroll
        for (int kk = 0; kk < 4; kk++) {
            const int i = (st - 11) * 4 + kk;
            wgmma_rs(p0, af + i * 4, dB(b16, wofs(st, kk)));
            if (kk == 0 && st < 14) {
                if (st == 12) mbar_wait(bars + 8 * (B_X15 + wg));
                ldfrag(st + 2);
            }
            if (!(i & 1) && CSP + i / 2 < 14) store_packed(o, CSP + i / 2, pk + (i / 2) * 4);
        }
    }
    wgmma_commit();
    asm volatile("bar.arrive %0, 256;" ::"r"(3 - wg) : "memory");
    wgmma_wait<0>();
    tb = clk();
#pragma unroll
    for (int h = 0; h < DSP; h++) { wait_until(tb, wg ? h * PSTD : PSB0 + h * PSTB); store_half(p0, o + 64 * F_, h); }
    if (wg == 0) {
#pragma unroll
        for (int h = DSP; h < 8; h++) { wait_until(tb, PSB0 + h * PSTB); store_half(p0, o + 64 * F_, h); }
    }
    asm volatile("bar.sync %0, 256;" ::"r"(2 + wg) : "memory");
    b16 = launder();
    wgmma_fence();
#pragma unroll
    for (int i = 0; i < 20; i++) {
        wgmma_rs(p1, af + i * 4, dB(b16, wofs(11 + (i >> 2), i & 3) + 128 * 16));
        if (!(i & 1) && DSP + i / 2 < 8) store_half(p0, o + 64 * F_, DSP + i / 2, wg);
    }
    wgmma_commit();
    asm volatile("bar.arrive %0, 256;" ::"r"(3 - wg) : "memory");
    wgmma_wait<0>();
#pragma unroll
    for (int h = 0; h < 4; h++) store_half(p1, o + 64 * F_ + 128, h);
    asm volatile("bar.sync %0, 256;" ::"r"(2 + wg) : "memory");
    wgmma_fence();
#pragma unroll
    for (int i = 0; i < 20; i++) wgmma_rs(p2, af + i * 4, dB(b16, wofs(11 + (i >> 2), i & 3) + 192 * 16));
    wgmma_commit();
    if (wg == 0) asm volatile("bar.arrive 3, 256;" ::: "memory");
    wgmma_wait<0>();
    store_half(p2, o + 64 * F_ + 192, 0);
    store_half(p2, o + 64 * F_ + 192, 1);
}

typedef CUresult (*EncodeTiledFn)(CUtensorMap*, CUtensorMapDataType, cuuint32_t, void*, const cuuint64_t*, const cuuint64_t*, const cuuint32_t*, const cuuint32_t*, CUtensorMapInterleave, CUtensorMapSwizzle, CUtensorMapL2promotion, CUtensorMapFloatOOBfill);

extern "C" void kernel_launch(void* const* d_in, const int* in_sizes, int n_in, void* d_out, int out_size) {
    static EncodeTiledFn enc = nullptr;
    static decltype(&fused_kernel<true>) kern = nullptr;
    static void *p_w = nullptr, *p_flags = nullptr;
    if (!enc) {
        void* fn = nullptr; cudaDriverEntryPointQueryResult qr;
        cudaGetDriverEntryPoint("cuTensorMapEncodeTiled", &fn, cudaEnableDefault, &qr);
        enc = (EncodeTiledFn)fn;
        int dev = 0, rsv = 0;
        cudaGetDevice(&dev);
        cudaDeviceGetAttribute(&rsv, cudaDevAttrReservedSharedMemoryPerBlock, dev);
        kern = rsv == 1024 && !NOHARD ? fused_kernel<true> : fused_kernel<false>;
        cudaFuncSetAttribute(kern, cudaFuncAttributeMaxDynamicSharedMemorySize, SMEM_BYTES);
        cudaGetSymbolAddress(&p_w, g_w);
        cudaGetSymbolAddress(&p_flags, g_flags);
    }
    CUtensorMap tmx, tmx64, tmq;
    {
        cuuint64_t gdim[2] = {(cuuint64_t)F_, (cuuint64_t)D_};
        cuuint64_t gstr[1] = {(cuuint64_t)F_ * 4};
        cuuint32_t box[2] = {(cuuint32_t)BN, 16};
        cuuint32_t estr[2] = {1, 1};
        enc(&tmq, CU_TENSOR_MAP_DATA_TYPE_INT32, 2, d_in[1], gdim, gstr, box, estr, CU_TENSOR_MAP_INTERLEAVE_NONE,
            CU_TENSOR_MAP_SWIZZLE_NONE, CU_TENSOR_MAP_L2_PROMOTION_L2_128B, CU_TENSOR_MAP_FLOAT_OOB_FILL_NONE);
    }
    {
        cuuint64_t gdim[2] = {(cuuint64_t)D_, (cuuint64_t)S_};
        cuuint64_t gstr[1] = {(cuuint64_t)D_ * 2};
        cuuint32_t box[2] = {(cuuint32_t)BK, (cuuint32_t)BM};
        cuuint32_t estr[2] = {1, 1};
        enc(&tmx, CU_TENSOR_MAP_DATA_TYPE_BFLOAT16, 2, d_in[0], gdim, gstr, box, estr, CU_TENSOR_MAP_INTERLEAVE_NONE,
            CU_TENSOR_MAP_SWIZZLE_128B, CU_TENSOR_MAP_L2_PROMOTION_L2_128B, CU_TENSOR_MAP_FLOAT_OOB_FILL_NONE);
        box[1] = 64;
        enc(&tmx64, CU_TENSOR_MAP_DATA_TYPE_BFLOAT16, 2, d_in[0], gdim, gstr, box, estr, CU_TENSOR_MAP_INTERLEAVE_NONE,
            CU_TENSOR_MAP_SWIZZLE_128B, CU_TENSOR_MAP_L2_PROMOTION_L2_128B, CU_TENSOR_MAP_FLOAT_OOB_FILL_NONE);
    }
    kern<<<128, 256, SMEM_BYTES>>>((const int*)d_in[1], (const unsigned short*)d_in[2], (__nv_bfloat16*)d_out, (uint4*)p_w, (unsigned*)p_flags, tmq, tmx64, tmx
    );
}
```
